```python
import torch

def _softmax(x, axis=-1):
    return torch.softmax(x, dim=axis)
def _gelu(x):
    return torch.nn.functional.gelu(x, approximate="tanh")
def _silu(x):
    return torch.nn.functional.silu(x)
def _sigmoid(x):
    return torch.sigmoid(x)
def _layernorm(x, axis=-1, eps=1e-5):
    m = x.mean(dim=axis, keepdim=True)
    v = x.var(dim=axis, keepdim=True, unbiased=False)
    return (x - m) / torch.sqrt(v + eps)
def _scatter_add(tgt, idx, src, axis=0):
    return tgt.clone().index_add_(axis, idx, src)
def _segment_sum(src, seg, n):
    out = torch.zeros((n,) + src.shape[1:], dtype=src.dtype)
    return out.index_add_(0, seg, src)
def _pad(x, pw):
    flat = tuple(v for pair in reversed(pw) for v in pair)
    return torch.nn.functional.pad(x, flat)

kernel_name = 'gather_scatter__edge_featured_mpnn_gatedgcn__graph'

def setup_inputs():

    _w = (lambda a: (lambda t: t.to(torch.bfloat16) if t.is_floating_point() else t)(torch.as_tensor(a)))
    N, deg, D, De = 50000, 16, 64, max(0, 1)
    E = N * deg
    return {
        "x": _w((lambda *s: torch.randn(*s, dtype=torch.bfloat16) * 0.4)(N, D)),
        "e_attr": _w((lambda *s: torch.randn(*s, dtype=torch.bfloat16) * 0.8)(E, De)),
        "src": _w((lambda lo, hi, *s: torch.randint(lo, hi, s))(0, N, E).to(torch.int64)),
        "dst": _w((lambda lo, hi, *s: torch.randint(lo, hi, s))(0, N, E).to(torch.int64)),
        "w_a": _w((lambda *s: torch.randn(*s, dtype=torch.bfloat16) * 0.8)(D, D)),
        "w_b": _w((lambda *s: torch.randn(*s, dtype=torch.bfloat16) * 0.4)(D, D)),
        "w_c": _w((lambda *s: torch.randn(*s, dtype=torch.bfloat16) * 0.8)(De, D)),
        "w_u": _w((lambda *s: torch.randn(*s, dtype=torch.bfloat16) * 0.05)(D, D)),
        "w_v": _w((lambda *s: torch.randn(*s, dtype=torch.bfloat16) * 0.05)(D, D)),
    }

def reference(x, e_attr, src, dst, w_a, w_b, w_c, w_u, w_v):
    N, D = x.shape
    hv = x @ w_v
    g = x[dst] @ w_a + x[src] @ w_b + e_attr @ w_c
    eta = _sigmoid(g)
    denom = _segment_sum(eta, dst, N) + 1e-6
    eta_n = eta / denom[dst]
    agg = _segment_sum(eta_n * hv[src], dst, N)
    z = x @ w_u + agg
    relu_z = torch.where(z > 0, z, 0 * z)
    return x + relu_z
```

```cpp
#include <cuda_runtime.h>
#include <cuda_bf16.h>
#include <cuda_fp16.h>
#include <cuda.h>
#include <stdint.h>

#define PUBAT 2
#define STAT 0
#define FENCE 1

namespace {

constexpr int G = 132;
constexpr int NWG = 4;
constexpr int NTA = (NWG + 1) * 128;
constexpr int NT = NWG * 128;
constexpr int NW = NT / 32;
constexpr int NSLOT = 384;
constexpr int NROW = 380;
constexpr int NGRP = NSLOT / 8;
constexpr int GPW = NGRP / NWG;
static_assert(GPW % 2 == 0 && GPW <= 16, "groups");
constexpr int VPT = 12 / NWG;
constexpr int VWG = 128 * VPT;
constexpr int CHUNK_MAX = NT * VPT * 4;
constexpr int CAPC = 88;
constexpr int CV = 22;
constexpr int CX = CAPC - 3 * CV;
constexpr int BPR = NT / CV;
constexpr int NXT = BPR * CV;
constexpr int RND = (G + BPR - 1) / BPR;
constexpr int NSTEP = 8;
constexpr int TN = NSTEP * 8;
constexpr int TB = TN * 128;
constexpr int ACC = NSTEP * 2;
constexpr int CAP = 6784;
constexpr int CAPX = CAP + TN;
constexpr int MAXT = 40;
constexpr int OVF_CAP = 64;
constexpr int XROWS = NSLOT / NWG;

constexpr uint32_t SB = 1024;
constexpr int RING = 81920;
constexpr int SM_RING = 0;
constexpr int SM_TBL = SM_RING + RING;
constexpr int SM_ENT = SM_TBL + NROW * 256;
constexpr int EXT_SBO = 144;
constexpr int EXT_REG = NSTEP * EXT_SBO + 112;
constexpr int SM_EXT = SM_ENT + CHUNK_MAX * 6;
constexpr int SM_ID = SM_EXT + 2 * EXT_REG;
constexpr int SM_DEG = SM_ID + NSTEP * EXT_SBO;
constexpr int SM_DH = SM_DEG + 512 * 4;
constexpr int SM_LG = SM_DH + 64 * 4;
constexpr int SM_MASK = SM_LG + 64 * 4;
constexpr int SM_MISC = SM_MASK + NWG * MAXT * 4;
constexpr int SM_HIST = SM_MISC + 64;
constexpr int SM_NB = SM_HIST + 144 * 4;
constexpr int SM_GI = SM_NB + 512 * 4;
constexpr int SM_OVF = SM_GI + (NWG * GPW + 1) * 64;
constexpr int SM_BAR = SM_OVF + OVF_CAP * 8;
constexpr int SM_PIPE = SM_BAR + 96;
constexpr int SM_TOTAL = SM_PIPE + 128;
constexpr int SM_WA = SM_RING + NSLOT * 128;
static_assert(SM_TOTAL <= 232448 && SM_PIPE % 32 == 0, "smem");
static_assert(SM_WA + 32768 <= RING && NWG * 2 * TB <= RING && SM_TBL % 1024 == 0, "ring");
static_assert((G + 1) * CAPC * 8 <= NROW * 256, "cells alias the table");
static_assert(CAPX * 4 <= CHUNK_MAX * 6, "edge slices alias the schedule");
static_assert(SM_ENT % 16 == 0 && SM_EXT % 16 == 0 && SM_ID % 16 == 0 && SM_DEG % 16 == 0 && SM_HIST % 16 == 0 && SM_GI % 16 == 0, "vector access");
static_assert(NSLOT * 128 * 4 <= SM_TOTAL, "slow path");

__device__ uint4 g_cell[G * G * CV];
__device__ uint2 g_ext[G * G * CX];
__device__ __align__(128) uint4 g_x16[2 * G * NSLOT * 8];
__device__ uint32_t g_cnt[64];
#define PROFT(i, t)
#define PROF(i) PROFT(i, 0)

constexpr uint32_t DEN0 = 0x10321032u;
constexpr uint32_t DEN_SMALL = 0x228e228eu;
constexpr uint32_t E_PAD = 0xffff0000u;
constexpr uint32_t H_MAX = 0x5c00u;
constexpr uint32_t H_MIN = 0x2800u;

__device__ __forceinline__ float tanh_(float x) { float y; asm("tanh.approx.f32 %0, %1;" : "=f"(y) : "f"(x)); return y; }
__device__ __forceinline__ float rcp(float x) { float y; asm("rcp.approx.ftz.f32 %0, %1;" : "=f"(y) : "f"(x)); return y; }
__device__ __forceinline__ uint32_t pack_bf16(float lo, float hi) { uint32_t r; asm("cvt.rn.bf16x2.f32 %0, %1, %2;" : "=r"(r) : "f"(hi), "f"(lo)); return r; }
__device__ __forceinline__ uint32_t pack_h(float lo, float hi) { uint32_t r; asm("cvt.rn.f16x2.f32 %0, %1, %2;" : "=r"(r) : "f"(hi), "f"(lo)); return r; }
__device__ __forceinline__ float h_lo(uint32_t v) { return __low2float(*reinterpret_cast<__half2*>(&v)); }
__device__ __forceinline__ float h_hi(uint32_t v) { return __high2float(*reinterpret_cast<__half2*>(&v)); }
__device__ __forceinline__ uint32_t hadd2(uint32_t a, uint32_t b) { uint32_t r; asm("add.rn.f16x2 %0, %1, %2;" : "=r"(r) : "r"(a), "r"(b)); return r; }
__device__ __forceinline__ uint32_t hsub2(uint32_t a, uint32_t b) { uint32_t r; asm("sub.rn.f16x2 %0, %1, %2;" : "=r"(r) : "r"(a), "r"(b)); return r; }
__device__ __forceinline__ uint32_t hfma2(uint32_t a, uint32_t b, uint32_t c) { uint32_t r; asm("fma.rn.f16x2 %0, %1, %2, %3;" : "=r"(r) : "r"(a), "r"(b), "r"(c)); return r; }
__device__ __forceinline__ uint32_t hamax2(uint32_t a, uint32_t b) { uint32_t r; asm("max.NaN.xorsign.abs.f16x2 %0, %1, %2;" : "=r"(r) : "r"(a), "r"(b)); return r; }
__device__ __forceinline__ uint32_t hmag(uint32_t m) { return max(m & 0x7fffu, (m >> 16) & 0x7fffu); }
__device__ __forceinline__ float bf_lo(uint32_t v) { return __uint_as_float(v << 16); }
__device__ __forceinline__ float bf_hi(uint32_t v) { return __uint_as_float(v & 0xffff0000u); }
__device__ __forceinline__ uint32_t bf2h(uint32_t v) { return pack_h(bf_lo(v), bf_hi(v)); }
__device__ __forceinline__ uint32_t finish2(uint32_t agg, uint32_t u, uint32_t x) {
    uint32_t z, o;
    asm("fma.rn.relu.bf16x2 %0, %1, %2, %3;" : "=r"(z) : "r"(agg), "r"(0x3f803f80u), "r"(u));
    asm("add.rn.bf16x2 %0, %1, %2;" : "=r"(o) : "r"(z), "r"(x));
    return o;
}
__device__ __forceinline__ char* row_ptr(const char* base, uint32_t row) {
    uint64_t a;
    asm("mad.wide.u32 %0, %1, 128, %2;" : "=l"(a) : "r"(row), "l"(base));
    return reinterpret_cast<char*>(a);
}
__device__ __forceinline__ uint32_t opaque32(uint32_t v) { asm volatile("" : "+r"(v)); return v; }
__device__ __forceinline__ uint32_t lds16(uint32_t a) { uint32_t v; asm volatile("ld.shared.u16 %0, [%1];" : "=r"(v) : "r"(a)); return v; }
__device__ __forceinline__ uint2 lds64(uint32_t a) { uint2 v; asm("ld.shared.v2.u32 {%0,%1}, [%2];" : "=r"(v.x), "=r"(v.y) : "r"(a)); return v; }
__device__ __forceinline__ uint2 lds64v(uint32_t a) { uint2 v; asm volatile("ld.shared.v2.u32 {%0,%1}, [%2];" : "=r"(v.x), "=r"(v.y) : "r"(a)); return v; }
__device__ __forceinline__ uint4 lds128(uint32_t a) {
    uint4 v;
    asm("ld.shared.v4.u32 {%0,%1,%2,%3}, [%4];" : "=r"(v.x), "=r"(v.y), "=r"(v.z), "=r"(v.w) : "r"(a));
    return v;
}
__device__ __forceinline__ uint32_t ldg32(const void* p) { uint32_t v; asm("ld.global.nc.u32 %0, [%1];" : "=r"(v) : "l"(p)); return v; }
template <class T> __device__ __forceinline__ T* opaque(T* p) { asm("" : "+l"(p)); return p; }

__device__ __forceinline__ void wg_fence() { asm volatile("wgmma.fence.sync.aligned;" ::: "memory"); }
__device__ __forceinline__ void wg_commit() { asm volatile("wgmma.commit_group.sync.aligned;" ::: "memory"); }
template <int N> __device__ __forceinline__ void wg_wait() { asm volatile("wgmma.wait_group.sync.aligned %0;" ::"n"(N) : "memory"); }
__device__ __forceinline__ void proxy_fence() { asm volatile("fence.proxy.async.shared::cta;" ::: "memory"); }
__device__ __forceinline__ void cp_commit() { asm volatile("cp.async.commit_group;" ::: "memory"); }
template <int N> __device__ __forceinline__ void cp_wait() { asm volatile("cp.async.wait_group %0;" ::"n"(N) : "memory"); }
__device__ __forceinline__ void cp16(uint32_t dst, const void* src) { asm volatile("cp.async.cg.shared.global [%0], [%1], 16;" ::"r"(dst), "l"(src) : "memory"); }
__device__ __forceinline__ void wg_bar(int id) { asm volatile("bar.sync %0, 128;" ::"r"(id) : "memory"); }
__device__ __forceinline__ void cta_bar() { __syncthreads(); }
__device__ __forceinline__ void edge_bar() { asm volatile("bar.sync 6, %0;" ::"n"(NT) : "memory"); }
__device__ __forceinline__ void node_bar() { asm volatile("bar.sync 7, %0;" ::"n"(NSLOT) : "memory"); }
__device__ __forceinline__ void wait_count(const uint32_t* c, uint32_t target) {
    for (uint32_t it = 0;; it++) {
        uint32_t v;
        asm volatile("ld.acquire.gpu.global.u32 %0, [%1];" : "=r"(v) : "l"(c) : "memory");
        if (v == target) break;
        if (it > (1u << 22)) __trap();
    }
}
__device__ __forceinline__ void bulk_load(uint32_t dst, const void* src, uint32_t bytes, uint32_t bar) {
    asm volatile("cp.async.bulk.shared::cluster.global.mbarrier::complete_tx::bytes [%0], [%1], %2, [%3];"
                 ::"r"(dst), "l"(src), "r"(bytes), "r"(bar) : "memory");
}
__device__ __forceinline__ void expect_tx(uint32_t bar, uint32_t bytes) {
    asm volatile("mbarrier.arrive.expect_tx.shared::cta.b64 _, [%0], %1;" ::"r"(bar), "r"(bytes) : "memory");
}
__device__ __forceinline__ bool mbar_try(uint32_t bar, uint32_t parity) {
    uint32_t ok;
    asm volatile("{\n.reg .pred q;\nmbarrier.try_wait.parity.shared::cta.b64 q, [%1], %2;\nselp.u32 %0, 1, 0, q;\n}"
                 : "=r"(ok) : "r"(bar), "r"(parity) : "memory");
    return ok;
}
__device__ __forceinline__ void mbar_wait(uint32_t bar, uint32_t parity = 0) {
    if (mbar_try(bar, parity)) return;
    for (uint32_t it = 0; !mbar_try(bar, parity); it++)
        if (it > (1u << 22)) __trap();
}
__device__ __forceinline__ void mbar_arrive(uint32_t bar) { asm volatile("mbarrier.arrive.shared::cta.b64 _, [%0];" ::"r"(bar) : "memory"); }
__device__ __forceinline__ uint4 ld_relaxed16(const uint4* p) {
    uint4 v;
    asm volatile("{\n.reg .b128 t;\n.reg .b64 a, b;\nld.relaxed.gpu.global.b128 t, [%4];\nmov.b128 {a, b}, t;\n"
                 "mov.b64 {%0, %1}, a;\nmov.b64 {%2, %3}, b;\n}"
                 : "=r"(v.x), "=r"(v.y), "=r"(v.z), "=r"(v.w) : "l"(p) : "memory");
    return v;
}
__device__ __forceinline__ void st_relaxed16(uint4* p, uint4 v) {
    asm volatile("{\n.reg .b128 t;\n.reg .b64 a, b;\nmov.b64 a, {%1, %2};\nmov.b64 b, {%3, %4};\nmov.b128 t, {a, b};\n"
                 "st.relaxed.gpu.global.b128 [%0], t;\n}"
                 ::"l"(p), "r"(v.x), "r"(v.y), "r"(v.z), "r"(v.w) : "memory");
}

#define F8(d, o) "+f"(d[o]), "+f"(d[o + 1]), "+f"(d[o + 2]), "+f"(d[o + 3]), "+f"(d[o + 4]), "+f"(d[o + 5]), "+f"(d[o + 6]), "+f"(d[o + 7])
#define R4(d, o) "+r"(d[o]), "+r"(d[o + 1]), "+r"(d[o + 2]), "+r"(d[o + 3])
#define L16 "%0,%1,%2,%3,%4,%5,%6,%7,%8,%9,%10,%11,%12,%13,%14,%15"
#define L20 L16 ",%16,%17,%18,%19"
#define L24 L20 ",%20,%21,%22,%23"
#define L32 L24 ",%24,%25,%26,%27,%28,%29,%30,%31"
constexpr uint32_t HI_SW = 0x40000000u | 64u;
constexpr uint32_t HI_E = EXT_SBO >> 4;
template <int A>
__device__ __forceinline__ void mma_ss(float (&d)[32], uint32_t alo, uint32_t blo) {
    asm volatile("{\n.reg .b64 a, b;\nmov.b64 a, {%32, %34};\nmov.b64 b, {%33, %34};\n"
                 "wgmma.mma_async.sync.aligned.m64n64k16.f32.f16.f16 {" L32 "}, a, b, %35, 1, 1, 1, 0;\n}\n"
                 : F8(d, 0), F8(d, 8), F8(d, 16), F8(d, 24)
                 : "r"(alo), "r"(blo), "r"(HI_SW), "n"(A));
}
template <int A, int T>
__device__ __forceinline__ void mma_rs(uint32_t (&d)[16], const uint32_t* a, uint32_t blo, uint32_t bhi) {
    asm volatile("{\n.reg .b64 b;\nmov.b64 b, {%20, %21};\n"
                 "wgmma.mma_async.sync.aligned.m64n64k16.f16.f16.f16 {" L16 "}, {%16,%17,%18,%19}, b, %22, 1, 1, %23;\n}\n"
                 : R4(d, 0), R4(d, 4), R4(d, 8), R4(d, 12)
                 : "r"(a[0]), "r"(a[1]), "r"(a[2]), "r"(a[3]), "r"(blo), "r"(bhi), "n"(A), "n"(T));
}
template <int A, int T>
__device__ __forceinline__ void mma_rs(uint32_t (&d)[20], const uint32_t* a, uint32_t blo, uint32_t bhi) {
    asm volatile("{\n.reg .b64 b;\nmov.b64 b, {%24, %25};\n"
                 "wgmma.mma_async.sync.aligned.m64n80k16.f16.f16.f16 {" L20 "}, {%20,%21,%22,%23}, b, %26, 1, 1, %27;\n}\n"
                 : R4(d, 0), R4(d, 4), R4(d, 8), R4(d, 12), R4(d, 16)
                 : "r"(a[0]), "r"(a[1]), "r"(a[2]), "r"(a[3]), "r"(blo), "r"(bhi), "n"(A), "n"(T));
}
template <int A, int T>
__device__ __forceinline__ void mma_rs(uint32_t (&d)[24], const uint32_t* a, uint32_t blo, uint32_t bhi) {
    asm volatile("{\n.reg .b64 b;\nmov.b64 b, {%28, %29};\n"
                 "wgmma.mma_async.sync.aligned.m64n96k16.f16.f16.f16 {" L24 "}, {%24,%25,%26,%27}, b, %30, 1, 1, %31;\n}\n"
                 : R4(d, 0), R4(d, 4), R4(d, 8), R4(d, 12), R4(d, 16), R4(d, 20)
                 : "r"(a[0]), "r"(a[1]), "r"(a[2]), "r"(a[3]), "r"(blo), "r"(bhi), "n"(A), "n"(T));
}
template <int R> __device__ __forceinline__ void keep(uint32_t (&d)[R]) {
#pragma unroll
    for (int i = 0; i < R; i++) asm volatile("" : "+r"(d[i])::"memory");
}
template <int R> __device__ __forceinline__ void keep(float (&d)[R]) {
#pragma unroll
    for (int i = 0; i < R; i++) asm volatile("" : "+f"(d[i])::"memory");
}
__device__ __forceinline__ void ldsm_t(uint32_t* f, uint32_t addr) {
    asm volatile("ldmatrix.sync.aligned.m8n8.x4.trans.shared.b16 {%0,%1,%2,%3}, [%4];"
                 : "=r"(f[0]), "=r"(f[1]), "=r"(f[2]), "=r"(f[3]) : "r"(addr) : "memory");
}
__device__ __forceinline__ uint32_t stage_w(unsigned char* mat, int k, int c, uint4 a, uint4 b, float s) {
    unsigned char* row = mat + k * 128;
    const uint4 e = make_uint4(pack_h(s * bf_lo(a.x), s * bf_lo(a.y)), pack_h(s * bf_lo(a.z), s * bf_lo(a.w)),
                               pack_h(s * bf_lo(b.x), s * bf_lo(b.y)), pack_h(s * bf_lo(b.z), s * bf_lo(b.w)));
    const uint4 o = make_uint4(pack_h(s * bf_hi(a.x), s * bf_hi(a.y)), pack_h(s * bf_hi(a.z), s * bf_hi(a.w)),
                               pack_h(s * bf_hi(b.x), s * bf_hi(b.y)), pack_h(s * bf_hi(b.z), s * bf_hi(b.w)));
    *reinterpret_cast<uint4*>(row + ((c ^ (k & 7)) << 4)) = e;
    *reinterpret_cast<uint4*>(row + (((c + 1) ^ (k & 7)) << 4)) = o;
    return hamax2(hamax2(hamax2(e.x, e.y), hamax2(e.z, e.w)), hamax2(hamax2(o.x, o.y), hamax2(o.z, o.w)));
}

struct Params {
    const __nv_bfloat16* x;
    const __nv_bfloat16* e;
    const int* src;
    const int* dst;
    const __nv_bfloat16 *wa, *wb, *wc, *wu, *wv;
    __nv_bfloat16* out;
    uint4* cell;
    uint2* ext;
    uint32_t* cnt;
    const uint4* x16;
    int N, E, npc, chunk;
    uint32_t magic;
};

__device__ __noinline__ void slow_bin(const Params& p, unsigned char* sm, int node0, int nvalid) {
    float* acc = reinterpret_cast<float*>(sm);
    const int tid = threadIdx.x, lane = tid & 31, warp = tid >> 5;
    edge_bar();
    for (int i = tid; i < NSLOT * 128; i += NT) acc[i] = 0.f;
    edge_bar();
    const uint32_t* x2 = reinterpret_cast<const uint32_t*>(p.x);
    const uint32_t* wb = reinterpret_cast<const uint32_t*>(p.wb) + lane;
    const uint32_t* wv = reinterpret_cast<const uint32_t*>(p.wv) + lane;
    const uint32_t* wa = reinterpret_cast<const uint32_t*>(p.wa) + lane;
    const uint32_t* wu = reinterpret_cast<const uint32_t*>(p.wu) + lane;
    const uint32_t wc = reinterpret_cast<const uint32_t*>(p.wc)[lane];
    for (int i0 = warp * 32; i0 < p.E; i0 += NT) {
        const int dl = i0 + lane < p.E ? p.dst[i0 + lane] - node0 : -1;
        uint32_t m = __ballot_sync(0xffffffffu, (uint32_t)dl < (uint32_t)nvalid);
        while (m) {
            const int l = __ffs(m) - 1;
            m &= m - 1;
            const int d = __shfl_sync(0xffffffffu, dl, l);
            const uint32_t xs = x2[p.src[i0 + l] * 32 + lane], xd = x2[(node0 + d) * 32 + lane];
            float g0 = 0.f, g1 = 0.f, v0 = 0.f, v1 = 0.f;
#pragma unroll 4
            for (int k = 0; k < 32; k++) {
                const uint32_t a = __shfl_sync(0xffffffffu, xs, k), b = __shfl_sync(0xffffffffu, xd, k);
#pragma unroll
                for (int h = 0; h < 2; h++) {
                    const float fs = h ? bf_hi(a) : bf_lo(a), fd = h ? bf_hi(b) : bf_lo(b);
                    const uint32_t ua = wa[(2 * k + h) * 32], ub = wb[(2 * k + h) * 32], uv = wv[(2 * k + h) * 32];
                    g0 += fd * bf_lo(ua) + fs * bf_lo(ub);
                    g1 += fd * bf_hi(ua) + fs * bf_hi(ub);
                    v0 += fs * bf_lo(uv);
                    v1 += fs * bf_hi(uv);
                }
            }
            const float ev = __bfloat162float(p.e[i0 + l]);
            const float e0 = 1.f / (1.f + expf(-(g0 + ev * bf_lo(wc))));
            const float e1 = 1.f / (1.f + expf(-(g1 + ev * bf_hi(wc))));
            float* a = acc + d * 128 + 2 * lane;
            atomicAdd(a, e0);
            atomicAdd(a + 1, e1);
            atomicAdd(a + 64, e0 * v0);
            atomicAdd(a + 65, e1 * v1);
        }
    }
    edge_bar();
    for (int n = warp; n < nvalid; n += NW) {
        const uint32_t xd = x2[(node0 + n) * 32 + lane];
        float u0 = 0.f, u1 = 0.f;
#pragma unroll 4
        for (int k = 0; k < 32; k++) {
            const uint32_t b = __shfl_sync(0xffffffffu, xd, k);
            const uint32_t w0 = wu[(2 * k) * 32], w1 = wu[(2 * k + 1) * 32];
            u0 += bf_lo(b) * bf_lo(w0) + bf_hi(b) * bf_lo(w1);
            u1 += bf_lo(b) * bf_hi(w0) + bf_hi(b) * bf_hi(w1);
        }
        const float* a = acc + n * 128 + 2 * lane;
        const float z0 = u0 + a[64] / (a[0] + 1e-6f), z1 = u1 + a[65] / (a[1] + 1e-6f);
        const float r0 = z0 > 0.f ? z0 : 0.f * z0, r1 = z1 > 0.f ? z1 : 0.f * z1;
        reinterpret_cast<uint32_t*>(p.out)[(node0 + n) * 32 + lane] = pack_bf16(bf_lo(xd) + r0, bf_hi(xd) + r1);
    }
}

__device__ __noinline__ void redo_small(const Params& p, const unsigned char* sm, uint32_t flags, int wg) {
    const int lane = threadIdx.x & 31, q = lane & 7;
    for (;;) {
        const uint32_t m = __ballot_sync(0xffffffffu, flags != 0);
        if (!m) break;
        const int l = __ffs(m) - 1;
        const uint32_t k = __ffs(__shfl_sync(0xffffffffu, flags, l)) - 1;
        if (lane == l) flags &= flags - 1;
        const uint2 gi = reinterpret_cast<const uint2*>(sm + SM_GI)[(wg * GPW + (k & 15) - (16 - GPW)) * 8 + 2 * (l & 3) + (k >> 4)];
        if (gi.y & 1) continue;
        const uint32_t pr = ((threadIdx.x >> 5) & 3) * 8 + (l >> 2);
        const uint32_t n = (gi.y >> 7) - blockIdx.x * p.npc;
        const uint32_t deg = reinterpret_cast<const uint32_t*>(sm + SM_DEG)[n];
        const uint32_t base = reinterpret_cast<const uint32_t*>(sm + SM_NB)[n] >> 2;
        const uint2 t = lds64(gi.x ^ (pr * 8));
        uint32_t wb[8], wv[8];
#pragma unroll
        for (int i = 0; i < 8; i++) {
            wb[i] = ldg32(reinterpret_cast<const uint32_t*>(p.wb) + (8 * q + i) * 32 + pr);
            wv[i] = ldg32(reinterpret_cast<const uint32_t*>(p.wv) + (8 * q + i) * 32 + pr);
        }
        const uint32_t wc = ldg32(reinterpret_cast<const uint32_t*>(p.wc) + pr);
        const uint32_t x = ldg32(reinterpret_cast<const uint32_t*>(p.x) + (gi.y >> 2) + pr);
        float d0 = 0.f, d1 = 0.f, n0 = 0.f, n1 = 0.f;
        for (uint32_t i0 = 0; i0 < deg; i0 += 16) {
            uint4 xr[4];
            float ev[4];
#pragma unroll
            for (int u = 0; u < 4; u++) {
                const uint32_t i = min(i0 + 4 * u + (lane >> 3), deg - 1);
                const uint32_t en = reinterpret_cast<const uint32_t*>(sm + SM_ENT)[base + 8 * i];
                ev[u] = h_hi(en);
                xr[u] = __ldg(reinterpret_cast<const uint4*>(p.x) + (en & 0xffff) * 8 + q);
            }
#pragma unroll
            for (int u = 0; u < 4; u++) {
                const uint32_t xw[4] = {xr[u].x, xr[u].y, xr[u].z, xr[u].w};
                float b0 = 0.f, b1 = 0.f, v0 = 0.f, v1 = 0.f;
#pragma unroll
                for (int j = 0; j < 8; j++) {
                    const float f = (j & 1) ? bf_hi(xw[j >> 1]) : bf_lo(xw[j >> 1]);
                    b0 += f * bf_lo(wb[j]); b1 += f * bf_hi(wb[j]);
                    v0 += f * bf_lo(wv[j]); v1 += f * bf_hi(wv[j]);
                }
#pragma unroll
                for (int o = 1; o < 8; o <<= 1) {
                    b0 += __shfl_xor_sync(0xffffffffu, b0, o); b1 += __shfl_xor_sync(0xffffffffu, b1, o);
                    v0 += __shfl_xor_sync(0xffffffffu, v0, o); v1 += __shfl_xor_sync(0xffffffffu, v1, o);
                }
                const float on = i0 + 4 * u + (lane >> 3) < deg ? 1.f : 0.f;
                const float e0 = __fdividef(on, 1.f + __expf(-(2.f * h_lo(t.x) + b0 + ev[u] * bf_lo(wc))));
                const float e1 = __fdividef(on, 1.f + __expf(-(2.f * h_hi(t.x) + b1 + ev[u] * bf_hi(wc))));
                d0 += e0; d1 += e1; n0 += e0 * v0; n1 += e1 * v1;
            }
        }
#pragma unroll
        for (int o = 8; o < 32; o <<= 1) {
            d0 += __shfl_xor_sync(0xffffffffu, d0, o); d1 += __shfl_xor_sync(0xffffffffu, d1, o);
            n0 += __shfl_xor_sync(0xffffffffu, n0, o); n1 += __shfl_xor_sync(0xffffffffu, n1, o);
        }
        if (lane == l)
            reinterpret_cast<uint32_t*>(p.out)[(gi.y >> 2) + pr] = finish2(pack_bf16(n0 * rcp(d0 + 1e-6f), n1 * rcp(d1 + 1e-6f)), t.y, x);
    }
}

template <int MODE>
__global__ void __launch_bounds__(NTA, 1) gatedgcn_kernel(const __grid_constant__ Params p, const __grid_constant__ CUtensorMap xmap,
                                                          const __grid_constant__ CUtensorMap hmap) {
    extern __shared__ __align__(1024) unsigned char sm[];
    constexpr uint32_t sb = SB;
    if ((uint32_t)__cvta_generic_to_shared(sm) != SB) __trap();
    const int tid = threadIdx.x, lane = tid & 31;
    const int warp = __shfl_sync(0xffffffffu, tid >> 5, 0);
    const int wg = warp >> 2, w4 = warp & 3, g8 = lane >> 2, t4 = lane & 3, tw = tid & 127;
    const int cta = blockIdx.x;
    const int node0 = cta * p.npc;
    const int nvalid = min(p.npc, p.N - node0);
    const int ch = 16 * w4 + 2 * g8;

    uint32_t* s_hist = reinterpret_cast<uint32_t*>(sm + SM_HIST);
    uint32_t* s_deg = reinterpret_cast<uint32_t*>(sm + SM_DEG);
    uint32_t* s_nb = reinterpret_cast<uint32_t*>(sm + SM_NB);
    uint2* s_gi = reinterpret_cast<uint2*>(sm + SM_GI);
    uint32_t* s_dh = reinterpret_cast<uint32_t*>(sm + SM_DH);
    uint32_t* s_lg = reinterpret_cast<uint32_t*>(sm + SM_LG);
    uint32_t* s_mask = reinterpret_cast<uint32_t*>(sm + SM_MASK);
    uint2* s_ovf = reinterpret_cast<uint2*>(sm + SM_OVF);
    uint32_t* s_misc = reinterpret_cast<uint32_t*>(sm + SM_MISC);
    uint32_t* s_ent = reinterpret_cast<uint32_t*>(sm + SM_ENT);

    PROF(0);
    if (wg == NWG) {
        uint32_t cnt1 = 0;
        if (MODE == 3) asm volatile("ld.relaxed.gpu.global.u32 %0, [%1];" : "=r"(cnt1) : "l"(p.cnt + 32 + opaque32(0)) : "memory");
        uint32_t mw = 0;
        if (MODE & 2) {
            for (int i = tw; i < (SM_DEG - SM_EXT) / 16; i += 128) {
                const int r = i - 2 * EXT_REG / 16, k = r % (EXT_SBO / 16);
                const uint32_t one = r >= 0 ? 0x3c00u << (16 * (k & 1)) : 0u;
                reinterpret_cast<uint4*>(sm + SM_EXT)[i] = make_uint4(k >> 1 == 0 ? one : 0, k >> 1 == 1 ? one : 0, k >> 1 == 2 ? one : 0, k >> 1 == 3 ? one : 0);
            }
#pragma unroll 1
            for (int hf = 0; hf < 2; hf++) {
                uint4 wr[4][2];
#pragma unroll
                for (int j = 0; j < 4; j++) {
                    const __nv_bfloat16* w = j == 0 ? p.wa : j == 1 ? p.wu : j == 2 ? p.wb : p.wv;
                    wr[j][0] = __ldg(reinterpret_cast<const uint4*>(w) + (hf * 128 + tw) * 2);
                    wr[j][1] = __ldg(reinterpret_cast<const uint4*>(w) + (hf * 128 + tw) * 2 + 1);
                }
#pragma unroll
                for (int j = 0; j < 4; j++)
                    mw = hamax2(mw, stage_w(sm + SM_WA + j * 8192, (hf * 128 + tw) >> 2, (tw & 3) * 2, wr[j][0], wr[j][1], j == 2 ? 0.5f : 1.f));
            }
            mw = hamax2(mw, bf2h(__ldg(reinterpret_cast<const uint32_t*>(p.wc) + lane)));
        }
        asm volatile("bar.sync 8, %0;" ::"n"(NTA) : "memory");
        uint32_t mx = 0;
        auto store_x = [&](int b) {
            asm volatile("cp.async.bulk.tensor.2d.global.shared::cta.bulk_group [%0, {%2, %3}], [%1];"
                         ::"l"(&hmap), "r"(sb + SM_RING + b * XROWS * 128), "r"(0), "r"(node0 + b * XROWS) : "memory");
            asm volatile("cp.async.bulk.commit_group;" ::: "memory");
        };
#pragma unroll 1
        for (int b = 0; b < NWG; b++) {
            mbar_wait(sb + SM_BAR + b * 24 + 16);
            uint4* xs = reinterpret_cast<uint4*>(sm + SM_RING + b * XROWS * 128) + tw;
            uint4 v[XROWS / 16];
#pragma unroll
            for (int j = 0; j < XROWS / 16; j++) v[j] = xs[128 * j];
#pragma unroll
            for (int j = 0; j < XROWS / 16; j++) {
                v[j].x = bf2h(v[j].x); v[j].y = bf2h(v[j].y); v[j].z = bf2h(v[j].z); v[j].w = bf2h(v[j].w);
                xs[128 * j] = v[j];
                mx = hamax2(mx, hamax2(hamax2(v[j].x, v[j].y), hamax2(v[j].z, v[j].w)));
            }
            proxy_fence();
            wg_bar(1 + NWG);
            if ((MODE == 1 || (MODE == 3 && STAT == 0)) && tw == 0) store_x(b);
        }
        if (MODE == 3 && STAT != 0 && w4 == 0) {
            asm volatile("bar.sync 10, 64;" ::: "memory");
            if (tw == 0) for (int b = 0; b < NWG; b++) store_x(b);
            __syncwarp();
        }
        PROFT(11, NT);
        if (!(MODE & 2)) {
            if (tw == 0) asm volatile("cp.async.bulk.wait_group 0;" ::: "memory");
            return;
        }
        if (hmag(hamax2(mx, mw)) > H_MAX) s_misc[4] = 1;
        if (hmag(mx) >= H_MIN) s_misc[2] = 1;
#pragma unroll 1
        for (int c = 0; c < NSLOT / 64; c++) {
            const uint32_t dx = (1u << 16) | ((sb + SM_RING + c * 8192) >> 4);
            constexpr uint32_t dw = (1u << 16) | ((sb + SM_WA) >> 4);
            float d0[32], d1[32];
            wg_fence();
            mma_ss<0>(d0, dw, dx);
            mma_ss<0>(d1, dw + 512, dx);
#pragma unroll
            for (int k = 1; k < 4; k++) { mma_ss<1>(d0, dw + 128 * k, dx + 2 * k); mma_ss<1>(d1, dw + 512 + 128 * k, dx + 2 * k); }
            wg_commit();
            if (MODE == 3 && c == PUBAT && tw == 0) {
                asm volatile("cp.async.bulk.wait_group 0;" ::: "memory");
                asm volatile("red.release.gpu.global.add.u32 [%0], %1;" ::"l"(p.cnt + 32), "r"(cta == 0 ? 1024 - G + 1 : 1) : "memory");
                PROFT(12, NT);
            }
            __syncwarp();
            wg_wait<0>();
            keep(d0); keep(d1);
            unsigned char* tb = sm + SM_TBL + (c * 64 + 2 * t4) * 256 + ((ch * 4) ^ (t4 << 5));
#pragma unroll
            for (int j = 0; j < 8; j++)
#pragma unroll
                for (int h = 0; h < 2; h++)
                    if (j < 7 || c * 64 + 8 * j + 2 * t4 + h < NROW)
                        *reinterpret_cast<uint2*>(tb + (8 * j + h) * 256) =
                            make_uint2(pack_h(0.5f * d0[4 * j + h], 0.5f * d0[4 * j + 2 + h]), pack_bf16(d1[4 * j + h], d1[4 * j + 2 + h]));
        }
        PROFT(13, NT);
        asm volatile("setmaxnreg.dec.sync.aligned.u32 32;");
        if (MODE == 3 && tw == 0) wait_count(p.cnt + 32, ((cnt1 >> 10) + 1) << 10);
        PROFT(15, NT);
        cta_bar();
        if (s_misc[5] | s_misc[4] | (s_misc[2] ^ 1)) return;
        const uint32_t step0 = s_misc[8 + w4];
        const int T = (s_misc[9 + w4] - step0 + NSTEP - 1) / NSTEP;
        const int q = lane >> 3, c8 = lane & 7;
        uint32_t pipe = sb + SM_PIPE + w4 * 32;
        uint32_t sidx = sb + SM_ENT + step0 * 32 + q * 8;
        uint32_t sd0 = sb + SM_RING + w4 * (2 * TB) + q * 256 + ((c8 ^ (2 * q)) << 4);
        uint32_t se = sb + SM_EXT + (w4 >> 1) * EXT_REG + (w4 & 1) * 64 + c8 * EXT_SBO + q * 4;
        const uint32_t xlo = (uint32_t)reinterpret_cast<uint64_t>(p.x16) + c8 * 16;
        const uint32_t xhi = (uint32_t)(reinterpret_cast<uint64_t>(p.x16) >> 32);
#pragma unroll 1
        for (int i = 0; i < T; i++) {
            const uint32_t st = i & 1;
            uint2 nx[NSTEP];
            const uint2 ee = lds64v(sidx + 32 * c8);
#pragma unroll
            for (int j = 0; j < NSTEP; j++) nx[j] = lds64v(sidx + 32 * j);
            const uint32_t e2 = __byte_perm(ee.x, ee.y, 0x7632);
            uint32_t pm;
            asm("set.nan.u32.f16x2 %0, %1, %1;" : "=r"(pm) : "r"(e2));
            mbar_wait(pipe + 16, ((i >> 1) & 1) ^ 1);
            asm volatile("st.shared.u32 [%0], %1;" ::"r"(se), "r"(e2 & ~pm) : "memory");
            asm volatile("st.shared.u32 [%0+16], %1;" ::"r"(se), "r"(pm & 0x40004000u) : "memory");
#pragma unroll
            for (int u = 0; u < 2 * NSTEP; u++) {
                uint64_t ga;
                asm("{\n.reg .b32 lo;\ndp2a.lo.u32.u32 lo, %1, 0x80, %2;\nmov.b64 %0, {lo, %3};\n}"
                    : "=l"(ga) : "r"((u & 1) ? nx[u >> 1].y : nx[u >> 1].x), "r"(xlo), "r"(xhi));
                cp16((sd0 ^ ((u & 1) * 16)) + (u & 1) * 128 + (u >> 1) * 1024, reinterpret_cast<const void*>(ga));
            }
            cp_commit();
            sidx += TN * 4;
            sd0 ^= TB;
            se += st ? -32 : 32;
            cp_wait<0>();
            if (FENCE) proxy_fence();
            __syncwarp();
            if (lane == 0) mbar_arrive(pipe);
            pipe ^= 8;
        }
    } else {
        const uint32_t bar = sb + SM_BAR + wg * 24;
        const int e0 = cta * p.chunk + wg * VWG * 4;
        const int nvec = min(min(p.chunk - wg * VWG * 4, p.E - e0) >> 2, VWG);
        auto load_x = [&]() {
            if (tw == 0) {
                expect_tx(bar + 16, XROWS * 128);
                asm volatile("cp.async.bulk.tensor.2d.shared::cluster.global.mbarrier::complete_tx::bytes [%0], [%1, {%3, %4}], [%2];"
                             ::"r"(sb + SM_RING + wg * XROWS * 128), "l"(&xmap), "r"(bar + 16), "r"(0), "r"(node0 + wg * XROWS) : "memory");
            }
        };
        if (tw == 0) {
#pragma unroll
            for (int i = 0; i < 3; i++) asm volatile("mbarrier.init.shared::cta.b64 [%0], 1;" ::"r"(bar + i * 8) : "memory");
            proxy_fence();
            if (MODE & 1) {
                expect_tx(bar, nvec * 16);
                bulk_load(sb + SM_RING + wg * XROWS * 128, p.dst + e0, nvec * 16, bar);
            }
#pragma unroll
            for (int i = 0; i < 4; i++)
                asm volatile("mbarrier.init.shared::cta.b64 [%0], %1;" ::"r"(sb + SM_PIPE + wg * 32 + i * 8), "r"(i < 2 ? 1 : 4) : "memory");
        }
        if (MODE == 2) load_x();
        uint32_t cnt0;
        asm volatile("ld.relaxed.gpu.global.u32 %0, [%1];" : "=r"(cnt0) : "l"(p.cnt + opaque32(0)) : "memory");

        if (tid < (SM_HIST - SM_DEG) / 16) reinterpret_cast<uint4*>(sm + SM_DEG)[tid] = make_uint4(0, 0, 0, 0);
        if (tid < 144) s_hist[tid] = 1;
        if (tid < 512 - NSLOT) s_nb[NSLOT + tid] = 0x80000000u;
        if (tid < (NWG * GPW + 1) * 8) s_gi[tid] = make_uint2(sb + SM_TBL, node0 * 128);
        if (MODE & 1) {
            const uint32_t f = NSLOT + ((2 * tid) & 127);
#pragma unroll
            for (int j = 0; j < (G * CAPC / 2 + NT - 1) / NT; j++)
                if (tid + NT * j < G * CAPC / 2) reinterpret_cast<uint4*>(sm + SM_TBL)[tid + NT * j] = make_uint4(0, f, 0, f + 1);
            if (tw == 0) {
                expect_tx(bar + 8, nvec * 24);
                bulk_load(sb + SM_ENT + wg * VWG * 24, p.src + e0, nvec * 16, bar + 8);
                bulk_load(sb + SM_ENT + wg * VWG * 24 + VWG * 16, p.e + e0, nvec * 8, bar + 8);
            }
        }
        edge_bar();

        const uint32_t epoch = (cnt0 >> 10) + (MODE == 2 ? 0 : 1);
        const uint32_t tag5 = epoch << 27, tag23 = epoch << 9;
        const int xb = tid / CV, xi = tid - xb * CV;
        if (MODE & 1) {
            int4 dv[VPT];
            mbar_wait(bar);
#pragma unroll
            for (int j = 0; j < VPT; j++) dv[j] = reinterpret_cast<const int4*>(sm + SM_RING + wg * XROWS * 128)[tw + 128 * j];
            PROF(1);
            uint32_t key[VPT * 4];
#pragma unroll
            for (int j = 0; j < VPT; j++) {
                const bool ok = tw + 128 * j < nvec;
                const int d[4] = {dv[j].x, dv[j].y, dv[j].z, dv[j].w};
#pragma unroll
                for (int q = 0; q < 4; q++) {
                    const uint32_t b = ok ? __umulhi((uint32_t)d[q], p.magic) : G;
                    const uint32_t r = atomicAdd(&s_hist[b], 1u);
                    key[j * 4 + q] = (b * CAPC + min(r, CAPC - 1u)) | ((uint32_t)(d[q] - b * p.npc) << 16);
                }
            }
            proxy_fence();
            wg_bar(1 + wg);
            PROF(2);
            mbar_wait(bar + 8);
            load_x();
            uint2* stage = reinterpret_cast<uint2*>(sm + SM_TBL);
            uint32_t emax = 0;
#pragma unroll
            for (int j = 0; j < VPT; j++) {
                const uint4 sv = reinterpret_cast<const uint4*>(sm + SM_ENT + wg * VWG * 24)[tw + 128 * j];
                uint2 ev = reinterpret_cast<const uint2*>(sm + SM_ENT + wg * VWG * 24 + VWG * 16)[tw + 128 * j];
                ev.x = bf2h(ev.x); ev.y = bf2h(ev.y);
                if (tw + 128 * j < nvec) emax = hamax2(emax, hamax2(ev.x, ev.y));
                const uint32_t w0[4] = {__byte_perm(sv.x, ev.x, 0x5410), __byte_perm(sv.y, ev.x, 0x7610),
                                        __byte_perm(sv.z, ev.y, 0x5410), __byte_perm(sv.w, ev.y, 0x7610)};
#pragma unroll
                for (int q = 0; q < 4; q++) stage[key[j * 4 + q] & 0xffff] = make_uint2(w0[q], key[j * 4 + q] >> 16);
            }
            if (hmag(emax) > H_MAX) s_misc[3] = 0x10000;
            edge_bar();
            PROF(3);
            uint32_t big = 0;
            if (tid < NXT) {
                const uint2* st = stage + xb * CAPC + xi * 3;
                uint4* gc = p.cell + (xb * G + cta) * CV + xi;
                uint4 v[RND];
#pragma unroll
                for (int j = 0; j < RND; j++)
                    if (xb + BPR * j < G) {
                        const uint2 a = st[j * BPR * CAPC], b = st[j * BPR * CAPC + 1], c = st[j * BPR * CAPC + 2];
                        v[j] = make_uint4(a.x, b.x, c.x, a.y + b.y * 512 + c.y * 262144 + tag5);
                        if (xi == 0) v[j].x = s_hist[xb + BPR * j] + s_misc[3];
                    }
#pragma unroll
                for (int j = 0; j < RND; j++)
                    if (xb + BPR * j < G) {
                        st_relaxed16(gc + j * BPR * G * CV, v[j]);
                        big |= xi == 0 && v[j].x > 3 * CV ? 1u << j : 0u;
                    }
            }
            for (;;) {
                const uint32_t m = __ballot_sync(0xffffffffu, big != 0);
                if (!m) break;
                const int l = __ffs(m) - 1;
                const int b = __shfl_sync(0xffffffffu, xb + BPR * (__ffs(big) - 1), l);
                if (lane == l) big &= big - 1;
                if (lane < CX) {
                    const uint2 v = stage[b * CAPC + 3 * CV + lane];
                    asm volatile("st.relaxed.gpu.global.v2.u32 [%0], {%1,%2};" ::"l"(p.ext + (b * G + cta) * CX + lane), "r"(v.x), "r"(v.y | tag23) : "memory");
                }
            }
        }
        asm volatile("bar.sync 8, %0;" ::"n"(NTA) : "memory");
        if ((MODE & 1) && tid == 0) asm volatile("red.relaxed.gpu.global.add.u32 [%0], %1;" ::"l"(p.cnt), "r"(cta == 0 ? 1024 - G + 1 : 1) : "memory");
        if (!(MODE & 2)) return;
        PROF(4);
        uint4 en[RND];
        uint32_t rk[RND];
        const uint4* gc = p.cell + cta * G * CV + tid;
        if (tid == 0) {
            for (uint32_t it = 0;; it++) {
                uint32_t c;
                asm volatile("ld.relaxed.gpu.global.u32 %0, [%1];" : "=r"(c) : "l"(p.cnt) : "memory");
                if (c == epoch << 10) break;
                if (it > (1u << 22)) __trap();
            }
        }
        edge_bar();
        if (MODE == 3 && STAT == 1 && warp == 0) asm volatile("bar.arrive 10, 64;" ::: "memory");
        PROF(5);
#pragma unroll
        for (int j = 0; j < RND; j++) {
            en[j] = make_uint4(0, 0, 0, tag5 | ((NSLOT + lane) * 0x40201u));
            if (tid < NXT && xb + BPR * j < G) en[j] = ld_relaxed16(gc + j * NXT);
        }
        for (uint32_t it = 0;; it++) {
            uint32_t miss = 0;
#pragma unroll
            for (int j = 0; j < RND; j++) miss |= en[j].w ^ tag5;
            if (miss < (1u << 27)) break;
#pragma unroll
            for (int j = 0; j < RND; j++)
                if ((en[j].w ^ tag5) >= (1u << 27)) en[j] = ld_relaxed16(gc + j * NXT);
            if (it > (1u << 20)) __trap();
        }
        __syncwarp();
        if (MODE == 3 && STAT == 2 && warp == 0) asm volatile("bar.arrive 10, 64;" ::: "memory");
        PROF(6);
        uint32_t big = 0;
#pragma unroll
        for (int j = 0; j < RND; j++) {
            big |= xi == 0 && en[j].x > 3 * CV ? 1u << j : 0u;
            uint32_t r[3];
#pragma unroll
            for (int s = 0; s < 3; s++) {
                const uint32_t d4 = (s == 0 ? en[j].w << 2 : en[j].w >> (9 * s - 2)) & 0x7fc;
                asm volatile("atom.shared.add.u32 %0, [%1], 1;" : "=r"(r[s]) : "r"(sb + SM_DEG + d4) : "memory");
            }
            rk[j] = r[0] + r[1] * 1024 + r[2] * 1048576;
        }
        for (;;) {
            const uint32_t m = __ballot_sync(0xffffffffu, big != 0);
            if (!m) break;
            const int l = __ffs(m) - 1;
            const int ps = __shfl_sync(0xffffffffu, xb + BPR * (__ffs(big) - 1), l);
            if (lane == l) big &= big - 1;
            const uint32_t c = __ldcg(&p.cell[(cta * G + ps) * CV].x);
            uint2 v = make_uint2(0, 0);
            if (lane < CX) asm volatile("ld.relaxed.gpu.global.v2.u32 {%0,%1}, [%2];" : "=r"(v.x), "=r"(v.y) : "l"(p.ext + (cta * G + ps) * CX + lane) : "memory");
            if (c > CAPC) s_misc[0] = 1;
            else if (3 * CV + lane < c) {
                for (uint32_t it = 0; (v.y ^ tag23) > 0x1ff; it++) {
                    asm volatile("ld.relaxed.gpu.global.v2.u32 {%0,%1}, [%2];" : "=r"(v.x), "=r"(v.y) : "l"(p.ext + (cta * G + ps) * CX + lane) : "memory");
                    if (it > (1u << 22)) __trap();
                }
                const uint32_t r = atomicAdd(&s_deg[v.y & 0x1ff], 1u);
                const uint32_t o = atomicAdd(&s_misc[1], 1u);
                if (o < OVF_CAP) s_ovf[o] = make_uint2(v.x, (v.y & 0x1ff) | (r << 16)); else s_misc[0] = 1;
            }
            __syncwarp();
        }
        edge_bar();
        PROF(7);
        if (warp < NSLOT / 32) {
            const uint32_t dg = s_deg[tid];
            if (dg > 62) s_misc[0] = 1;
            const uint32_t kb = tid < nvalid ? 62 - min(dg, 62u) : 63;
            const uint32_t r = atomicAdd(&s_dh[kb], 1u);
            node_bar();
            const uint2 h = reinterpret_cast<const uint2*>(s_dh)[lane];
            uint32_t inc = h.x + h.y;
#pragma unroll
            for (int o = 1; o < 32; o <<= 1) { const uint32_t v = __shfl_up_sync(0xffffffffu, inc, o); if (lane >= o) inc += v; }
            const uint32_t pe = __shfl_sync(0xffffffffu, inc - h.x - h.y, kb >> 1), po = __shfl_sync(0xffffffffu, inc - h.y, kb >> 1);
            const uint32_t pos = ((kb & 1) ? po : pe) + r;
            const uint32_t grp = pos >> 3, slot = pos & 7, row = grp / NWG, col = grp - row * NWG;
            const uint32_t seg = (row & 1) ? NWG - 1 - col : col;
            const uint32_t idx = seg * GPW + row;
            if (slot == 0) s_lg[idx] = max(dg, (uint32_t)NSTEP);
            node_bar();
            const uint2 l = reinterpret_cast<const uint2*>(s_lg)[lane];
            uint32_t in2 = l.x + l.y;
#pragma unroll
            for (int o = 1; o < 32; o <<= 1) { const uint32_t v = __shfl_up_sync(0xffffffffu, in2, o); if (lane >= o) in2 += v; }
            const uint32_t ex2 = in2 - l.x - l.y;
            const uint32_t mine = __shfl_sync(0xffffffffu, ex2, (lane / (GPW / 2)) * (GPW / 2));
            const uint32_t ee = __shfl_sync(0xffffffffu, in2 - l.y, idx >> 1), eo = __shfl_sync(0xffffffffu, in2, idx >> 1);
            const uint32_t sbeg = __shfl_sync(0xffffffffu, ex2, seg * (GPW / 2));
            if (__any_sync(0xffffffffu, in2 > CAP / 8 || in2 - mine > MAXT * NSTEP) || s_misc[0] != 0) {
                s_misc[5] = 1;
            } else {
                const uint32_t gend = (idx & 1) ? eo : ee;
                const uint32_t first = gend - dg;
                s_nb[tid] = first * 32 + slot * 4;
                s_gi[idx * 8 + slot] = tid < nvalid ? make_uint2(sb + SM_TBL + tid * 256 + (((tid >> 1) & 3) << 5), (node0 + tid) * 128)
                                                    : make_uint2(sb + SM_TBL, node0 * 128 + 1);
                if (slot == 0) {
                    const uint32_t last = gend - 1 - sbeg;
                    s_mask[seg * MAXT + last / NSTEP] = last % NSTEP + 1;
                }
                if (tid <= NWG * (GPW / 2) && tid % (GPW / 2) == 0) s_misc[8 + tid / (GPW / 2)] = ex2;
                for (uint32_t s = gend - s_lg[idx]; s < first; s++) s_ent[s * 8 + slot] = node0 | (tid < nvalid ? E_PAD : 0u);
                const uint32_t tot = __shfl_sync(0xffffffffu, in2, 31);
                if (tid < TN) s_ent[tot * 8 + tid] = node0;
            }
        }
        edge_bar();
        PROF(8);
        if (s_misc[5] == 0) {
            uint32_t at[RND * 3];
#pragma unroll
            for (int j = 0; j < RND; j++)
#pragma unroll
                for (int s = 0; s < 3; s++) {
                    const uint32_t d4 = (s == 0 ? en[j].w << 2 : en[j].w >> (9 * s - 2)) & 0x7fc;
                    asm volatile("ld.shared.u32 %0, [%1];" : "=r"(at[3 * j + s]) : "r"(sb + SM_NB + d4));
                }
#pragma unroll
            for (int j = 0; j < RND; j++)
#pragma unroll
                for (int s = 0; s < 3; s++) {
                    const uint32_t w = s == 0 ? en[j].x : s == 1 ? en[j].y : en[j].z;
                    const uint32_t r32 = (s == 0 ? rk[j] << 5 : rk[j] >> (10 * s - 5)) & 0x7fe0;
                    asm volatile("{\n.reg .pred q;\nsetp.ge.s32 q, %0, 0;\n@q st.shared.u32 [%0+%2], %1;\n}"
                                 ::"r"(at[3 * j + s] + r32), "r"(w), "n"(sb + SM_ENT));
                }
            if (tid < s_misc[1]) {
                const uint2 v = s_ovf[tid];
                s_ent[(s_nb[v.y & 0xffff] >> 2) + (v.y >> 16) * 8] = v.x;
            }
        }
        asm volatile("setmaxnreg.inc.sync.aligned.u32 112;");
        uint32_t fb[16], fv[16], fe[4];
        {
            const uint32_t wc = __ldg(reinterpret_cast<const uint32_t*>(p.wc) + (ch >> 1));
            const uint32_t a = sb + SM_WA + 16384 + ((lane >> 4) * 8 + (lane & 7)) * 128 + (((2 * w4 + ((lane >> 3) & 1)) ^ (lane & 7)) << 4);
#pragma unroll
            for (int k = 0; k < 4; k++) {
                ldsm_t(fb + 4 * k, a + k * 2048);
                ldsm_t(fv + 4 * k, a + 8192 + k * 2048);
            }
            const uint32_t wh = pack_h(0.5f * bf_lo(wc), 0.5f * bf_hi(wc));
            fe[0] = t4 ? 0 : __byte_perm(wh, 0xfb53, 0x5410);
            fe[1] = t4 ? 0 : __byte_perm(wh, 0xfb53, 0x5432);
        }
        proxy_fence();
        cta_bar();
        PROF(9);
        if (s_misc[5] | s_misc[4] | (s_misc[2] ^ 1)) { slow_bin(p, sm, node0, nvalid); return; }
        const uint32_t step0 = __shfl_sync(0xffffffffu, s_misc[8 + wg], 0), nstep = __shfl_sync(0xffffffffu, s_misc[9 + wg], 0) - step0;
        const int T = (nstep + NSTEP - 1) / NSTEP;
        uint32_t pipe = sb + SM_PIPE + wg * 32;
        uint32_t dx = (1u << 16) | ((sb + SM_RING + wg * (2 * TB)) >> 4);
        const uint32_t ea = (SM_EXT >> 4) + (wg >> 1) * (EXT_REG >> 4) + (wg & 1) * 4;
        uint32_t de = (((SM_ID >> 4) - ea) << 16) | ((sb >> 4) + ea);
        const uint32_t de2 = 2 * de + 2 - (2 << 16);
        uint32_t ma = sb + SM_MASK + wg * MAXT * 4;

        uint32_t hN[2], hD[2], hA[2];
        uint32_t u2[2], x2[2], nd[2], flags = 0, nmax = 0;
        uint32_t gptr = opaque32(sb + SM_GI + wg * GPW * 64 + t4 * 16);
        const uint32_t tb4 = opaque32(ch * 4);
        auto init_group = [&]() {
            const uint4 gi = lds128(gptr);
            gptr += 64;
            const uint2 t0 = lds64(gi.x ^ tb4), t1 = lds64(gi.z ^ tb4);
            nd[0] = gi.y + (tb4 >> 1); nd[1] = gi.w + (tb4 >> 1);
            x2[0] = ldg32(reinterpret_cast<const char*>(p.x) + (nd[0] & ~1u));
            x2[1] = ldg32(reinterpret_cast<const char*>(p.x) + (nd[1] & ~1u));
            u2[0] = t0.y; u2[1] = t1.y;
            const uint32_t a0 = __byte_perm(t0.x, t1.x, 0x5410), a1 = __byte_perm(t0.x, t1.x, 0x7632);
            hA[0] = hsub2(a0, fe[2]); hA[1] = hsub2(a1, fe[3]);
            fe[2] = a0; fe[3] = a1;
            hN[0] = hN[1] = 0; hD[0] = hD[1] = DEN0;
        };
        auto flush_group = [&]() {
            const uint32_t o0 = finish2(pack_bf16(h_lo(hN[0]) * rcp(h_lo(hD[0])), h_lo(hN[1]) * rcp(h_lo(hD[1]))), u2[0], x2[0]);
            const uint32_t o1 = finish2(pack_bf16(h_hi(hN[0]) * rcp(h_hi(hD[0])), h_hi(hN[1]) * rcp(h_hi(hD[1]))), u2[1], x2[1]);
            asm volatile("{\n.reg .pred q;\nsetp.eq.u32 q, %2, 0;\n@q st.global.u32 [%0], %1;\n}" ::"l"(reinterpret_cast<char*>(p.out) + nd[0]), "r"(o0), "r"(nd[0] & 1) : "memory");
            asm volatile("{\n.reg .pred q;\nsetp.eq.u32 q, %2, 0;\n@q st.global.u32 [%0], %1;\n}" ::"l"(reinterpret_cast<char*>(p.out) + nd[1]), "r"(o1), "r"(nd[1] & 1) : "memory");
            nmax = hamax2(nmax, hamax2(hN[0], hN[1]));
            flags = (flags >> 1) | (~(__vminu2(hD[0], hD[1]) + (0x80008000u - DEN_SMALL)) & 0x80008000u);
        };
        uint32_t db[ACC], dv_[ACC];
        auto step = [&](int j, bool fix) {
#pragma unroll
            for (int r = 0; r < 2; r++) {
                const uint32_t g = fix ? hadd2(db[2 * j + r], hA[r]) : db[2 * j + r];
                const uint32_t w = pack_h(fmaf(tanh_(h_lo(g)), 256.f, 256.f), fmaf(tanh_(h_hi(g)), 256.f, 256.f));
                hD[r] = hadd2(hD[r], w);
                hN[r] = hfma2(w, dv_[2 * j + r], hN[r]);
            }
        };
        fe[2] = fe[3] = 0;
        init_group();
#pragma unroll 1
        for (int i = 0; i < T; i++) {
            uint32_t m;
            asm volatile("ld.shared.u32 %0, [%1];" : "=r"(m) : "r"(ma));
            ma += 4;
            mbar_wait(pipe, (i >> 1) & 1);
            wg_fence();
            mma_rs<0, 0>(dv_, fv, dx, HI_SW);
            mma_rs<0, 0>(db, fb, dx, HI_SW);
#pragma unroll
            for (int k = 1; k < 4; k++) {
                mma_rs<1, 0>(dv_, fv + 4 * k, dx + 2 * k, HI_SW);
                mma_rs<1, 0>(db, fb + 4 * k, dx + 2 * k, HI_SW);
            }
            mma_rs<1, 1>(db, fe, de, HI_E);
            wg_commit();
            dx ^= TB >> 4;
            de = de2 - de;
            auto block = [&](int e) {
                wg_wait<0>();
                keep(db); keep(dv_); keep(fe);
                if (lane == 0) mbar_arrive(pipe + 16);
#pragma unroll
                for (int j = 0; j < NSTEP; j++) {
                    step(j, e > 0 && j >= e);
                    if (j + 1 == e) { flush_group(); init_group(); }
                }
            };
            if (m == 0) block(0);
            else switch (m) {
                case 1: block(1); break;
                case 2: block(2); break;
                case 3: block(3); break;
                case 4: block(4); break;
                case 5: block(5); break;
                case 6: block(6); break;
                case 7: block(7); break;
                default: block(8); break;
            }
            pipe ^= 8;
        }
        PROF(10);
        if (__any_sync(0xffffffffu, flags != 0)) redo_small(p, sm, flags, wg);
        uint32_t over;
        asm volatile("{\n.reg .pred q;\nsetp.ge.u32 q, %1, 0x7c00;\nbar.red.or.pred q, 9, %2, q;\nselp.u32 %0, 1, 0, q;\n}"
                     : "=r"(over) : "r"(hmag(nmax)), "n"(NT) : "memory");
        if (over) slow_bin(p, sm, node0, nvalid);
        PROF(14);
    }
}

typedef CUresult (*EncodeFn)(CUtensorMap*, CUtensorMapDataType, cuuint32_t, void*, const cuuint64_t*, const cuuint64_t*,
                             const cuuint32_t*, const cuuint32_t*, CUtensorMapInterleave, CUtensorMapSwizzle,
                             CUtensorMapL2promotion, CUtensorMapFloatOOBfill);

}

extern "C" void kernel_launch(void* const* d_in, const int* in_sizes, int n_in, void* d_out, int out_size) {
    static int sms = 0;
    static EncodeFn encode = nullptr;
    static void *cell = nullptr, *ext = nullptr, *cnt = nullptr, *x16 = nullptr;
    if (!sms) {
        int dev = 0;
        cudaGetDevice(&dev);
        cudaDeviceGetAttribute(&sms, cudaDevAttrMultiProcessorCount, dev);
        cudaFuncSetAttribute(gatedgcn_kernel<1>, cudaFuncAttributeMaxDynamicSharedMemorySize, SM_TOTAL);
        cudaFuncSetAttribute(gatedgcn_kernel<2>, cudaFuncAttributeMaxDynamicSharedMemorySize, SM_TOTAL);
        cudaFuncSetAttribute(gatedgcn_kernel<3>, cudaFuncAttributeMaxDynamicSharedMemorySize, SM_TOTAL);
        cudaDriverEntryPointQueryResult qr;
        cudaGetDriverEntryPoint("cuTensorMapEncodeTiled", (void**)&encode, cudaEnableDefault, &qr);
        cudaGetSymbolAddress(&cell, g_cell);
        cudaGetSymbolAddress(&ext, g_ext);
        cudaGetSymbolAddress(&cnt, g_cnt);
        cudaGetSymbolAddress(&x16, g_x16);
        if (((uint64_t)x16 >> 32) != (((uint64_t)x16 + G * NSLOT * 128 - 1) >> 32)) x16 = (char*)x16 + G * NSLOT * 128;
    }
    Params p;
    p.x = (const __nv_bfloat16*)d_in[0];
    p.e = (const __nv_bfloat16*)d_in[1];
    p.src = (const int*)d_in[2];
    p.dst = (const int*)d_in[3];
    p.wa = (const __nv_bfloat16*)d_in[4];
    p.wb = (const __nv_bfloat16*)d_in[5];
    p.wc = (const __nv_bfloat16*)d_in[6];
    p.wu = (const __nv_bfloat16*)d_in[7];
    p.wv = (const __nv_bfloat16*)d_in[8];
    p.out = (__nv_bfloat16*)d_out;
    p.cell = (uint4*)cell;
    p.ext = (uint2*)ext;
    p.cnt = (uint32_t*)cnt;
    p.x16 = (const uint4*)x16;
    p.N = in_sizes[0] / 64;
    p.E = in_sizes[2];
    p.npc = (p.N + G - 1) / G;
    p.chunk = ((p.E + G - 1) / G + 7) & ~7;
    p.magic = (uint32_t)(0x100000000ull / (uint32_t)p.npc) + 1u;
    if (!encode || p.npc > NROW || p.N <= (G - 1) * p.npc || p.chunk > CHUNK_MAX || (p.E & 7) ||
        p.E - (G - 1) * p.chunk <= (NWG - 1) * VWG * 4) return;

    CUtensorMap xmap, hmap;
    const cuuint64_t dims[2] = {64, (cuuint64_t)p.N};
    const cuuint64_t strides[1] = {128};
    const cuuint32_t box[2] = {64, XROWS}, estr[2] = {1, 1};
    encode(&xmap, CU_TENSOR_MAP_DATA_TYPE_BFLOAT16, 2, d_in[0], dims, strides, box, estr, CU_TENSOR_MAP_INTERLEAVE_NONE,
           CU_TENSOR_MAP_SWIZZLE_128B, CU_TENSOR_MAP_L2_PROMOTION_L2_256B, CU_TENSOR_MAP_FLOAT_OOB_FILL_NONE);
    encode(&hmap, CU_TENSOR_MAP_DATA_TYPE_FLOAT16, 2, x16, dims, strides, box, estr, CU_TENSOR_MAP_INTERLEAVE_NONE,
           CU_TENSOR_MAP_SWIZZLE_128B, CU_TENSOR_MAP_L2_PROMOTION_NONE, CU_TENSOR_MAP_FLOAT_OOB_FILL_NONE);
    if (sms >= G) {
        gatedgcn_kernel<3><<<G, NTA, SM_TOTAL>>>(p, xmap, hmap);
    } else {
        gatedgcn_kernel<1><<<G, NTA, SM_TOTAL>>>(p, xmap, hmap);
        gatedgcn_kernel<2><<<G, NTA, SM_TOTAL>>>(p, xmap, hmap);
    }
}
```

```cpp
#include <cuda_runtime.h>
#include <cuda_bf16.h>
#include <cuda_fp16.h>
#include <cuda.h>
#include <stdint.h>

#define DELAY 1
#define HOLD 0
#define TOKEN 1
#define SNAKE 1
#define AHEAD 0
#define XPOS 2
#define REDAT 3
#define REDTH 480
#define ONEBAR 1
#define NTOK (ONEBAR ? 288 : 256)
#define PINC 1
#define PFT 1
#define HSM 0
#define CVV 24
#define EFIRST 0
#define WEAK 0
#define FENCE 1

namespace {

constexpr int G = 132;
constexpr int NWG = 4;
constexpr int NTA = (NWG + 1) * 128;
constexpr int NT = NWG * 128;
constexpr int NW = NT / 32;
constexpr int NSLOT = 384;
constexpr int NROW = 380;
constexpr int NGRP = NSLOT / 8;
constexpr int GPW = NGRP / NWG;
static_assert(GPW % 2 == 0 && GPW <= 16 && G <= 192, "groups");
constexpr int VPT = 12 / NWG;
constexpr int VWG = 128 * VPT;
constexpr int CHUNK_MAX = NT * VPT * 4;
constexpr int CAPC = 88;
constexpr int CV = CVV;
constexpr int CX = CAPC - 3 * CV;
constexpr int BPR = NT / CV;
constexpr int NXT = BPR * CV;
constexpr int RND = (G + BPR - 1) / BPR;
constexpr int NSTEP = 8;
constexpr int RNC = (G * CV + NT - 1) / NT;
constexpr int TN = NSTEP * 8;
constexpr int TB = TN * 128;
constexpr int ACC = NSTEP * 2;
constexpr int CAP = 6784;
constexpr int CAPX = CAP + TN;
constexpr int MAXT = 40;
constexpr int OVF_CAP = 64;
constexpr int XROWS = NSLOT / NWG;

constexpr uint32_t SB = 1024;
constexpr int RING = 81920;
constexpr int SM_RING = 0;
constexpr int SM_TBL = SM_RING + RING;
constexpr int SM_ENT = SM_TBL + NROW * 256;
constexpr int SM_EXT = SM_ENT + CHUNK_MAX * 6;
constexpr int SM_DEG = SM_EXT + 4096;
constexpr int SM_DH = SM_DEG + 512 * 4;
constexpr int SM_LG = SM_DH + 64 * 4;
constexpr int SM_MASK = SM_LG + 64 * 4;
constexpr int SM_MISC = SM_MASK + NWG * MAXT * 4;
constexpr int SM_HIST = SM_MISC + 64;
constexpr int SM_NB = SM_HIST + 144 * 4;
constexpr int SM_GI = SM_NB + 512 * 4;
constexpr int SM_OVF = SM_GI + (NWG * GPW + 1) * 64;
constexpr int SM_BAR = SM_OVF + OVF_CAP * 8;
constexpr int SM_RDY = SM_BAR + 96;
constexpr int LND0 = 4 * NT * 16;
constexpr int SM_LND1 = SM_TBL + (NWG - 1) * XROWS * 256;
constexpr int SM_PIPE = SM_BAR + 128;
constexpr int SM_WC = SM_PIPE + 128;
constexpr int SM_TOTAL = SM_WC + 128;
constexpr int SM_WA = SM_RING + NSLOT * 128;
static_assert(SM_TOTAL <= 232448 && SM_PIPE % 32 == 0, "smem");
static_assert(SM_WA + 32768 <= RING && NWG * 2 * TB <= SM_WA + 16384 && SM_TBL % 1024 == 0, "ring");
static_assert((G + 1) * CAPC * 8 <= NROW * 256, "cells alias the table");
static_assert(CAPX * 4 <= CHUNK_MAX * 6 && LND0 <= CHUNK_MAX * 6 && SM_LND1 + G * CV * 16 - LND0 <= SM_ENT, "aliases");
static_assert(SM_ENT % 16 == 0 && (SB + SM_EXT) % 4096 < 2048 && SM_EXT % 1024 == 0 && SM_DEG % 16 == 0 && SM_HIST % 16 == 0 && SM_GI % 16 == 0, "vector access");
static_assert(NSLOT * 128 * 4 <= SM_TOTAL, "slow path");

__device__ uint4 g_cell[G * G * CV];
__device__ __align__(16) uint2 g_ext[G * G * CX];
__device__ __align__(128) uint4 g_x16[2 * G * NSLOT * 8];
__device__ uint32_t g_cnt[64];
#define PROFT(i, t)
#define PROF(i) PROFT(i, 0)

constexpr uint32_t DEN0 = 0x10321032u;
constexpr uint32_t DEN_SMALL = 0x228e228eu;
constexpr uint32_t E_PAD = 0xffff0000u;
constexpr uint32_t H_MAX = 0x4ff0u;
constexpr uint32_t H_MIN = 0x2800u;

__device__ __forceinline__ float tanh_(float x) { float y; asm("tanh.approx.f32 %0, %1;" : "=f"(y) : "f"(x)); return y; }
__device__ __forceinline__ float rcp(float x) { float y; asm("rcp.approx.ftz.f32 %0, %1;" : "=f"(y) : "f"(x)); return y; }
__device__ __forceinline__ uint32_t pack_bf16(float lo, float hi) { uint32_t r; asm("cvt.rn.bf16x2.f32 %0, %1, %2;" : "=r"(r) : "f"(hi), "f"(lo)); return r; }
__device__ __forceinline__ uint32_t pack_h(float lo, float hi) { uint32_t r; asm("cvt.rn.f16x2.f32 %0, %1, %2;" : "=r"(r) : "f"(hi), "f"(lo)); return r; }
__device__ __forceinline__ float h_lo(uint32_t v) { return __low2float(*reinterpret_cast<__half2*>(&v)); }
__device__ __forceinline__ float h_hi(uint32_t v) { return __high2float(*reinterpret_cast<__half2*>(&v)); }
__device__ __forceinline__ uint32_t hadd2(uint32_t a, uint32_t b) { uint32_t r; asm("add.rn.f16x2 %0, %1, %2;" : "=r"(r) : "r"(a), "r"(b)); return r; }
__device__ __forceinline__ uint32_t hsub2(uint32_t a, uint32_t b) { uint32_t r; asm("sub.rn.f16x2 %0, %1, %2;" : "=r"(r) : "r"(a), "r"(b)); return r; }
__device__ __forceinline__ uint32_t hfma2(uint32_t a, uint32_t b, uint32_t c) { uint32_t r; asm("fma.rn.f16x2 %0, %1, %2, %3;" : "=r"(r) : "r"(a), "r"(b), "r"(c)); return r; }
__device__ __forceinline__ uint32_t hamax2(uint32_t a, uint32_t b) { uint32_t r; asm("max.NaN.xorsign.abs.f16x2 %0, %1, %2;" : "=r"(r) : "r"(a), "r"(b)); return r; }
__device__ __forceinline__ uint32_t hmag(uint32_t m) { return max(m & 0x7fffu, (m >> 16) & 0x7fffu); }
__device__ __forceinline__ float bf_lo(uint32_t v) { return __uint_as_float(v << 16); }
__device__ __forceinline__ float bf_hi(uint32_t v) { return __uint_as_float(v & 0xffff0000u); }
__device__ __forceinline__ uint32_t bf2h(uint32_t v) { return pack_h(bf_lo(v), bf_hi(v)); }
__device__ __forceinline__ uint32_t finish2(float n0, float d0, float n1, float d1, uint32_t u, uint32_t x) {
    uint32_t z, o;
    asm("cvt.rn.relu.bf16x2.f32 %0, %1, %2;" : "=r"(z) : "f"(fmaf(n1, rcp(d1), h_hi(u))), "f"(fmaf(n0, rcp(d0), h_lo(u))));
    asm("add.rn.bf16x2 %0, %1, %2;" : "=r"(o) : "r"(z), "r"(x));
    return o;
}
__device__ __forceinline__ char* row_ptr(const char* base, uint32_t row) {
    uint64_t a;
    asm("mad.wide.u32 %0, %1, 128, %2;" : "=l"(a) : "r"(row), "l"(base));
    return reinterpret_cast<char*>(a);
}
__device__ __forceinline__ uint32_t opaque32(uint32_t v) { asm volatile("" : "+r"(v)); return v; }
__device__ __forceinline__ uint32_t lds16(uint32_t a) { uint32_t v; asm volatile("ld.shared.u16 %0, [%1];" : "=r"(v) : "r"(a)); return v; }
__device__ __forceinline__ uint2 lds64(uint32_t a) { uint2 v; asm("ld.shared.v2.u32 {%0,%1}, [%2];" : "=r"(v.x), "=r"(v.y) : "r"(a)); return v; }
__device__ __forceinline__ uint2 lds64v(uint32_t a) { uint2 v; asm volatile("ld.shared.v2.u32 {%0,%1}, [%2];" : "=r"(v.x), "=r"(v.y) : "r"(a)); return v; }
__device__ __forceinline__ uint4 lds128(uint32_t a) {
    uint4 v;
    asm("ld.shared.v4.u32 {%0,%1,%2,%3}, [%4];" : "=r"(v.x), "=r"(v.y), "=r"(v.z), "=r"(v.w) : "r"(a));
    return v;
}
__device__ __forceinline__ uint32_t ldg32(const void* p) { uint32_t v; asm("ld.global.nc.u32 %0, [%1];" : "=r"(v) : "l"(p)); return v; }
template <class T> __device__ __forceinline__ T* opaque(T* p) { asm("" : "+l"(p)); return p; }

__device__ __forceinline__ void spin_limit(uint32_t it) {
    asm volatile("{\n.reg .pred q;\n.reg .b64 z;\nmov.b64 z, 0;\nsetp.gt.u32 q, %0, 0x400000;\n@q st.global.u32 [z], %0;\n}" ::"r"(it));
}
__device__ __forceinline__ void wg_fence() { asm volatile("wgmma.fence.sync.aligned;" ::: "memory"); }
__device__ __forceinline__ void wg_commit() { asm volatile("wgmma.commit_group.sync.aligned;" ::: "memory"); }
template <int N> __device__ __forceinline__ void wg_wait() { asm volatile("wgmma.wait_group.sync.aligned %0;" ::"n"(N) : "memory"); }
__device__ __forceinline__ void proxy_fence() { asm volatile("fence.proxy.async.shared::cta;" ::: "memory"); }
__device__ __forceinline__ void cp_commit() { asm volatile("cp.async.commit_group;" ::: "memory"); }
template <int N> __device__ __forceinline__ void cp_wait() { asm volatile("cp.async.wait_group %0;" ::"n"(N) : "memory"); }
__device__ __forceinline__ void cp16(uint32_t dst, const void* src) { asm volatile("cp.async.cg.shared.global [%0], [%1], 16;" ::"r"(dst), "l"(src) : "memory"); }
__device__ __forceinline__ void wg_bar(int id) { asm volatile("bar.sync %0, 128;" ::"r"(id) : "memory"); }
__device__ __forceinline__ void cta_bar() { __syncthreads(); }
__device__ __forceinline__ void edge_bar() { asm volatile("bar.sync 6, %0;" ::"n"(NT) : "memory"); }
__device__ __forceinline__ void node_bar() { asm volatile("bar.sync 7, %0;" ::"n"(NSLOT) : "memory"); }
__device__ __forceinline__ void wait_count(const uint32_t* c, uint32_t target) {
    for (uint32_t it = 0;; it++) {
        uint32_t v;
        asm volatile("ld.acquire.gpu.global.u32 %0, [%1];" : "=r"(v) : "l"(c) : "memory");
        if (v == target) break;
        spin_limit(it);
    }
}
__device__ __forceinline__ void bulk_load(uint32_t dst, const void* src, uint32_t bytes, uint32_t bar) {
    asm volatile("cp.async.bulk.shared::cluster.global.mbarrier::complete_tx::bytes [%0], [%1], %2, [%3];"
                 ::"r"(dst), "l"(src), "r"(bytes), "r"(bar) : "memory");
}
__device__ __forceinline__ void bulk_stream(uint32_t dst, const void* src, uint32_t bytes, uint32_t bar) {
    if (!EFIRST) { bulk_load(dst, src, bytes, bar); return; }
    asm volatile("{\n.reg .b64 pol;\ncreatepolicy.fractional.L2::evict_first.b64 pol, 1.0;\n"
                 "cp.async.bulk.shared::cluster.global.mbarrier::complete_tx::bytes.L2::cache_hint [%0], [%1], %2, [%3], pol;\n}"
                 ::"r"(dst), "l"(src), "r"(bytes), "r"(bar) : "memory");
}
__device__ __forceinline__ void expect_tx(uint32_t bar, uint32_t bytes) {
    asm volatile("mbarrier.arrive.expect_tx.shared::cta.b64 _, [%0], %1;" ::"r"(bar), "r"(bytes) : "memory");
}
__device__ __forceinline__ bool mbar_try(uint32_t bar, uint32_t parity) {
    uint32_t ok;
    asm volatile("{\n.reg .pred q;\nmbarrier.try_wait.parity.shared::cta.b64 q, [%1], %2;\nselp.u32 %0, 1, 0, q;\n}"
                 : "=r"(ok) : "r"(bar), "r"(parity) : "memory");
    return ok;
}
__device__ __forceinline__ bool mbar_test(uint32_t bar) {
    uint32_t ok;
    asm volatile("{\n.reg .pred q;\nmbarrier.test_wait.parity.shared::cta.b64 q, [%1], 0;\nselp.u32 %0, 1, 0, q;\n}"
                 : "=r"(ok) : "r"(bar) : "memory");
    return ok;
}
__device__ __forceinline__ void mbar_wait(uint32_t bar, uint32_t parity = 0) {
    if (mbar_try(bar, parity)) return;
    for (uint32_t it = 0; !mbar_try(bar, parity); it++)
        spin_limit(it);
}
__device__ __forceinline__ void mbar_arrive(uint32_t bar) { asm volatile("mbarrier.arrive.shared::cta.b64 _, [%0];" ::"r"(bar) : "memory"); }
__device__ __forceinline__ uint4 ld_relaxed16(const uint4* p) {
    uint4 v;
    asm volatile("{\n.reg .b128 t;\n.reg .b64 a, b;\nld.relaxed.gpu.global.b128 t, [%4];\nmov.b128 {a, b}, t;\n"
                 "mov.b64 {%0, %1}, a;\nmov.b64 {%2, %3}, b;\n}"
                 : "=r"(v.x), "=r"(v.y), "=r"(v.z), "=r"(v.w) : "l"(p) : "memory");
    return v;
}
__device__ __forceinline__ void ld_relaxed16_if(uint4& v, const uint4* p, bool on) {
    asm volatile("{\n.reg .pred q;\n.reg .b128 t;\n.reg .b64 a, b;\nsetp.ne.u32 q, %5, 0;\n"
                 "mov.b64 a, {%0, %1};\nmov.b64 b, {%2, %3};\nmov.b128 t, {a, b};\n@q ld.relaxed.gpu.global.b128 t, [%4];\n"
                 "mov.b128 {a, b}, t;\nmov.b64 {%0, %1}, a;\nmov.b64 {%2, %3}, b;\n}"
                 : "+r"(v.x), "+r"(v.y), "+r"(v.z), "+r"(v.w) : "l"(p), "r"((uint32_t)on) : "memory");
}
__device__ __forceinline__ void st_relaxed16(uint4* p, uint4 v) {
    asm volatile("{\n.reg .b128 t;\n.reg .b64 a, b;\nmov.b64 a, {%1, %2};\nmov.b64 b, {%3, %4};\nmov.b128 t, {a, b};\n"
                 "st.relaxed.gpu.global.b128 [%0], t;\n}"
                 ::"l"(p), "r"(v.x), "r"(v.y), "r"(v.z), "r"(v.w) : "memory");
}

#define F8(d, o) "+f"(d[o]), "+f"(d[o + 1]), "+f"(d[o + 2]), "+f"(d[o + 3]), "+f"(d[o + 4]), "+f"(d[o + 5]), "+f"(d[o + 6]), "+f"(d[o + 7])
#define R4(d, o) "+r"(d[o]), "+r"(d[o + 1]), "+r"(d[o + 2]), "+r"(d[o + 3])
#define L16 "%0,%1,%2,%3,%4,%5,%6,%7,%8,%9,%10,%11,%12,%13,%14,%15"
#define L20 L16 ",%16,%17,%18,%19"
#define L24 L20 ",%20,%21,%22,%23"
#define L48 L24 ",%24,%25,%26,%27,%28,%29,%30,%31,%32,%33,%34,%35,%36,%37,%38,%39,%40,%41,%42,%43,%44,%45,%46,%47"
constexpr uint32_t HI_SW = 0x40000000u | 64u;
template <int A>
__device__ __forceinline__ void mma_ss(uint32_t (&d)[24], uint32_t alo, uint32_t blo) {
    asm volatile("{\n.reg .b64 a, b;\nmov.b64 a, {%24, %26};\nmov.b64 b, {%25, %26};\n"
                 "wgmma.mma_async.sync.aligned.m64n96k16.f16.f16.f16 {" L24 "}, a, b, %27, 1, 1, 1, 0;\n}\n"
                 : R4(d, 0), R4(d, 4), R4(d, 8), R4(d, 12), R4(d, 16), R4(d, 20)
                 : "r"(alo), "r"(blo), "r"(HI_SW), "n"(A));
}
template <int A, int T>
__device__ __forceinline__ void mma_rs(uint32_t (&d)[16], const uint32_t* a, uint32_t blo, uint32_t bhi) {
    asm volatile("{\n.reg .b64 b;\nmov.b64 b, {%20, %21};\n"
                 "wgmma.mma_async.sync.aligned.m64n64k16.f16.f16.f16 {" L16 "}, {%16,%17,%18,%19}, b, %22, 1, 1, %23;\n}\n"
                 : R4(d, 0), R4(d, 4), R4(d, 8), R4(d, 12)
                 : "r"(a[0]), "r"(a[1]), "r"(a[2]), "r"(a[3]), "r"(blo), "r"(bhi), "n"(A), "n"(T));
}
template <int R> __device__ __forceinline__ void keep(uint32_t (&d)[R]) {
#pragma unroll
    for (int i = 0; i < R; i++) asm volatile("" : "+r"(d[i])::"memory");
}
template <int R> __device__ __forceinline__ void keep(float (&d)[R]) {
#pragma unroll
    for (int i = 0; i < R; i++) asm volatile("" : "+f"(d[i])::"memory");
}
__device__ __forceinline__ void ldsm_t(uint32_t* f, uint32_t addr) {
    asm volatile("ldmatrix.sync.aligned.m8n8.x4.trans.shared.b16 {%0,%1,%2,%3}, [%4];"
                 : "=r"(f[0]), "=r"(f[1]), "=r"(f[2]), "=r"(f[3]) : "r"(addr) : "memory");
}
__device__ __forceinline__ uint32_t stage_w(unsigned char* mat, int k, int c, uint4 a, uint4 b, float s) {
    unsigned char* row = mat + k * 128;
    const uint4 e = make_uint4(pack_h(s * bf_lo(a.x), s * bf_lo(a.y)), pack_h(s * bf_lo(a.z), s * bf_lo(a.w)),
                               pack_h(s * bf_lo(b.x), s * bf_lo(b.y)), pack_h(s * bf_lo(b.z), s * bf_lo(b.w)));
    const uint4 o = make_uint4(pack_h(s * bf_hi(a.x), s * bf_hi(a.y)), pack_h(s * bf_hi(a.z), s * bf_hi(a.w)),
                               pack_h(s * bf_hi(b.x), s * bf_hi(b.y)), pack_h(s * bf_hi(b.z), s * bf_hi(b.w)));
    *reinterpret_cast<uint4*>(row + ((c ^ (k & 7)) << 4)) = e;
    *reinterpret_cast<uint4*>(row + (((c + 1) ^ (k & 7)) << 4)) = o;
    return hamax2(hamax2(hamax2(e.x, e.y), hamax2(e.z, e.w)), hamax2(hamax2(o.x, o.y), hamax2(o.z, o.w)));
}

struct Params {
    const __nv_bfloat16* x;
    const __nv_bfloat16* e;
    const int* src;
    const int* dst;
    const __nv_bfloat16 *wa, *wb, *wc, *wu, *wv;
    __nv_bfloat16* out;
    uint4* cell;
    uint2* ext;
    uint32_t* cnt;
    const uint4* x16;
    int N, E, npc, chunk;
    uint32_t magic;
};

__device__ __noinline__ void slow_bin(const Params& p, unsigned char* sm, int node0, int nvalid) {
    float* acc = reinterpret_cast<float*>(sm);
    const int tid = threadIdx.x, lane = tid & 31, warp = tid >> 5;
    edge_bar();
    for (int i = tid; i < NSLOT * 128; i += NT) acc[i] = 0.f;
    edge_bar();
    const uint32_t* x2 = reinterpret_cast<const uint32_t*>(p.x);
    const uint32_t* wb = reinterpret_cast<const uint32_t*>(p.wb) + lane;
    const uint32_t* wv = reinterpret_cast<const uint32_t*>(p.wv) + lane;
    const uint32_t* wa = reinterpret_cast<const uint32_t*>(p.wa) + lane;
    const uint32_t* wu = reinterpret_cast<const uint32_t*>(p.wu) + lane;
    const uint32_t wc = reinterpret_cast<const uint32_t*>(p.wc)[lane];
    for (int i0 = warp * 32; i0 < p.E; i0 += NT) {
        const int dl = i0 + lane < p.E ? p.dst[i0 + lane] - node0 : -1;
        uint32_t m = __ballot_sync(0xffffffffu, (uint32_t)dl < (uint32_t)nvalid);
        while (m) {
            const int l = __ffs(m) - 1;
            m &= m - 1;
            const int d = __shfl_sync(0xffffffffu, dl, l);
            const uint32_t xs = x2[p.src[i0 + l] * 32 + lane], xd = x2[(node0 + d) * 32 + lane];
            float g0 = 0.f, g1 = 0.f, v0 = 0.f, v1 = 0.f;
#pragma unroll 4
            for (int k = 0; k < 32; k++) {
                const uint32_t a = __shfl_sync(0xffffffffu, xs, k), b = __shfl_sync(0xffffffffu, xd, k);
#pragma unroll
                for (int h = 0; h < 2; h++) {
                    const float fs = h ? bf_hi(a) : bf_lo(a), fd = h ? bf_hi(b) : bf_lo(b);
                    const uint32_t ua = wa[(2 * k + h) * 32], ub = wb[(2 * k + h) * 32], uv = wv[(2 * k + h) * 32];
                    g0 += fd * bf_lo(ua) + fs * bf_lo(ub);
                    g1 += fd * bf_hi(ua) + fs * bf_hi(ub);
                    v0 += fs * bf_lo(uv);
                    v1 += fs * bf_hi(uv);
                }
            }
            const float ev = __bfloat162float(p.e[i0 + l]);
            const float e0 = rcp(1.f + __expf(-(g0 + ev * bf_lo(wc))));
            const float e1 = rcp(1.f + __expf(-(g1 + ev * bf_hi(wc))));
            float* a = acc + d * 128 + 2 * lane;
            atomicAdd(a, e0);
            atomicAdd(a + 1, e1);
            atomicAdd(a + 64, e0 * v0);
            atomicAdd(a + 65, e1 * v1);
        }
    }
    edge_bar();
    for (int n = warp; n < nvalid; n += NW) {
        const uint32_t xd = x2[(node0 + n) * 32 + lane];
        float u0 = 0.f, u1 = 0.f;
#pragma unroll 4
        for (int k = 0; k < 32; k++) {
            const uint32_t b = __shfl_sync(0xffffffffu, xd, k);
            const uint32_t w0 = wu[(2 * k) * 32], w1 = wu[(2 * k + 1) * 32];
            u0 += bf_lo(b) * bf_lo(w0) + bf_hi(b) * bf_lo(w1);
            u1 += bf_lo(b) * bf_hi(w0) + bf_hi(b) * bf_hi(w1);
        }
        const float* a = acc + n * 128 + 2 * lane;
        const float z0 = u0 + a[64] * rcp(a[0] + 1e-6f), z1 = u1 + a[65] * rcp(a[1] + 1e-6f);
        const float r0 = z0 > 0.f ? z0 : 0.f * z0, r1 = z1 > 0.f ? z1 : 0.f * z1;
        reinterpret_cast<uint32_t*>(p.out)[(node0 + n) * 32 + lane] = pack_bf16(bf_lo(xd) + r0, bf_hi(xd) + r1);
    }
}

__device__ __noinline__ void redo_small(const Params& p, const unsigned char* sm, uint32_t flags, int wg) {
    const int lane = threadIdx.x & 31, q = lane & 7;
    for (;;) {
        const uint32_t m = __ballot_sync(0xffffffffu, flags != 0);
        if (!m) break;
        const int l = __ffs(m) - 1;
        const uint32_t k = __ffs(__shfl_sync(0xffffffffu, flags, l)) - 1;
        if (lane == l) flags &= flags - 1;
        const uint2 gi = reinterpret_cast<const uint2*>(sm + SM_GI)[(wg * GPW + (k & 15) - (16 - GPW)) * 8 + 2 * (l & 3) + (k >> 4)];
        if (gi.x & 8) continue;
        const uint32_t pr = ((threadIdx.x >> 5) & 3) * 8 + (l >> 2);
        const uint32_t n = (gi.x - SB - SM_TBL) >> 8, row = blockIdx.x * p.npc + n;
        const uint32_t deg = reinterpret_cast<const uint32_t*>(sm + SM_DEG)[n];
        const uint32_t base = (reinterpret_cast<const uint32_t*>(sm + SM_NB)[n] >> 2) - 8 * deg;
        const uint2 t = lds64(gi.x ^ (pr * 8));
        uint32_t wb[8], wv[8];
#pragma unroll
        for (int i = 0; i < 8; i++) {
            wb[i] = ldg32(reinterpret_cast<const uint32_t*>(p.wb) + (8 * q + i) * 32 + pr);
            wv[i] = ldg32(reinterpret_cast<const uint32_t*>(p.wv) + (8 * q + i) * 32 + pr);
        }
        const uint32_t wc = ldg32(reinterpret_cast<const uint32_t*>(p.wc) + pr);
        const uint32_t x = ldg32(reinterpret_cast<const uint32_t*>(p.x) + row * 32 + pr);
        float d0 = 0.f, d1 = 0.f, n0 = 0.f, n1 = 0.f;
        for (uint32_t i0 = 0; i0 < deg; i0 += 16) {
            uint4 xr[4];
            float ev[4];
#pragma unroll
            for (int u = 0; u < 4; u++) {
                const uint32_t i = min(i0 + 4 * u + (lane >> 3), deg - 1);
                const uint32_t en = reinterpret_cast<const uint32_t*>(sm + SM_ENT)[base + 8 * i];
                ev[u] = h_hi(en);
                xr[u] = __ldg(reinterpret_cast<const uint4*>(p.x) + (en & 0xffff) * 8 + q);
            }
#pragma unroll
            for (int u = 0; u < 4; u++) {
                const uint32_t xw[4] = {xr[u].x, xr[u].y, xr[u].z, xr[u].w};
                float b0 = 0.f, b1 = 0.f, v0 = 0.f, v1 = 0.f;
#pragma unroll
                for (int j = 0; j < 8; j++) {
                    const float f = (j & 1) ? bf_hi(xw[j >> 1]) : bf_lo(xw[j >> 1]);
                    b0 += f * bf_lo(wb[j]); b1 += f * bf_hi(wb[j]);
                    v0 += f * bf_lo(wv[j]); v1 += f * bf_hi(wv[j]);
                }
#pragma unroll
                for (int o = 1; o < 8; o <<= 1) {
                    b0 += __shfl_xor_sync(0xffffffffu, b0, o); b1 += __shfl_xor_sync(0xffffffffu, b1, o);
                    v0 += __shfl_xor_sync(0xffffffffu, v0, o); v1 += __shfl_xor_sync(0xffffffffu, v1, o);
                }
                const float on = i0 + 4 * u + (lane >> 3) < deg ? 1.f : 0.f;
                const float e0 = __fdividef(on, 1.f + __expf(-(2.f * h_lo(t.x) + b0 + ev[u] * bf_lo(wc))));
                const float e1 = __fdividef(on, 1.f + __expf(-(2.f * h_hi(t.x) + b1 + ev[u] * bf_hi(wc))));
                d0 += e0; d1 += e1; n0 += e0 * v0; n1 += e1 * v1;
            }
        }
#pragma unroll
        for (int o = 8; o < 32; o <<= 1) {
            d0 += __shfl_xor_sync(0xffffffffu, d0, o); d1 += __shfl_xor_sync(0xffffffffu, d1, o);
            n0 += __shfl_xor_sync(0xffffffffu, n0, o); n1 += __shfl_xor_sync(0xffffffffu, n1, o);
        }
        if (lane == l)
            reinterpret_cast<uint32_t*>(p.out)[row * 32 + pr] = finish2(n0, d0 + 1e-6f, n1, d1 + 1e-6f, t.y, x);
    }
}

template <int MODE>
__global__ void __launch_bounds__(NTA, 1) gatedgcn_kernel(const __grid_constant__ Params p, const __grid_constant__ CUtensorMap xmap,
                                                          const __grid_constant__ CUtensorMap hmap) {
    extern __shared__ __align__(1024) unsigned char sm[];
    constexpr uint32_t sb = SB;
    spin_limit((uint32_t)__cvta_generic_to_shared(sm) != SB ? ~0u : 0u);
    const int tid = threadIdx.x, lane = tid & 31;
    const int warp = __shfl_sync(0xffffffffu, tid >> 5, 0);
    const int wg = warp >> 2, w4 = warp & 3, g8 = lane >> 2, t4 = lane & 3, tw = tid & 127;
    const int cta = blockIdx.x;
    const int node0 = cta * p.npc;
    const int nvalid = min(p.npc, p.N - node0);
    const int ch = 16 * w4 + 2 * g8;
    const uint64_t xa = reinterpret_cast<uint64_t>(p.x) + (uint64_t)node0 * 128, oa = reinterpret_cast<uint64_t>(p.out) + (uint64_t)node0 * 128;
    const uint32_t xrow0 = (uint32_t)xa;

    uint32_t* s_hist = reinterpret_cast<uint32_t*>(sm + SM_HIST);
    uint32_t* s_deg = reinterpret_cast<uint32_t*>(sm + SM_DEG);
    uint32_t* s_nb = reinterpret_cast<uint32_t*>(sm + SM_NB);
    uint2* s_gi = reinterpret_cast<uint2*>(sm + SM_GI);
    uint32_t* s_dh = reinterpret_cast<uint32_t*>(sm + SM_DH);
    uint32_t* s_lg = reinterpret_cast<uint32_t*>(sm + SM_LG);
    uint32_t* s_mask = reinterpret_cast<uint32_t*>(sm + SM_MASK);
    uint2* s_ovf = reinterpret_cast<uint2*>(sm + SM_OVF);
    uint32_t* s_misc = reinterpret_cast<uint32_t*>(sm + SM_MISC);
    uint32_t* s_ent = reinterpret_cast<uint32_t*>(sm + SM_ENT);

    constexpr int NB10 = MODE == 3 && HOLD ? NTA : NT + 32;
    PROF(0);
    if (wg == NWG) {
        if (tw == 0) {
            asm volatile("mbarrier.init.shared::cta.b64 [%0], 1;" ::"r"(sb + SM_RDY + 8) : "memory");
            asm volatile("mbarrier.init.shared::cta.b64 [%0], 1;" ::"r"(sb + SM_RDY + 16) : "memory");
            proxy_fence();
            if (MODE & 2) {
                expect_tx(sb + SM_RDY + 8, 4 * 8192 + 128);
                bulk_load(sb + SM_WA, p.wa, 8192, sb + SM_RDY + 8);
                bulk_load(sb + SM_WA + 8192, p.wu, 8192, sb + SM_RDY + 8);
                bulk_load(sb + SM_WA + 16384, p.wb, 8192, sb + SM_RDY + 8);
                bulk_load(sb + SM_WA + 24576, p.wv, 8192, sb + SM_RDY + 8);
                bulk_load(sb + SM_WC, p.wc, 128, sb + SM_RDY + 8);
            }
        }
        if (PFT && tw == 32) {
            asm volatile("prefetch.tensormap [%0];" ::"l"(&xmap) : "memory");
            if (MODE & 1) asm volatile("prefetch.tensormap [%0];" ::"l"(&hmap) : "memory");
        }
        asm volatile("setmaxnreg.dec.sync.aligned.u32 32;");
        uint32_t mw = 0;
        if (MODE & 2) {
            {
                const int k = (tw >> 3) & 7;
                const uint32_t one = tw >= 64 ? 0x3c00u << (16 * (k & 1)) : 0u;
                const uint4 v = make_uint4(k >> 1 == 0 ? one : 0, k >> 1 == 1 ? one : 0, k >> 1 == 2 ? one : 0, k >> 1 == 3 ? one : 0);
                reinterpret_cast<uint4*>(sm + SM_EXT)[tw] = v;
                reinterpret_cast<uint4*>(sm + SM_EXT)[tw + 128] = v;
            }
            wg_bar(1 + NWG);
            mbar_wait(sb + SM_RDY + 8);
            if (w4 == 0) {
                mw = reinterpret_cast<uint32_t*>(sm + SM_WC)[lane];
                mw = pack_h(0.5f * bf_lo(mw), 0.5f * bf_hi(mw));
                reinterpret_cast<uint32_t*>(sm + SM_WC)[lane] = mw;
            }
#pragma unroll 1
            for (int j = 0; j < 8; j++) {
                const uint4* w = reinterpret_cast<const uint4*>(sm + SM_WA + j * 4096) + tw * 2;
                const uint4 a = w[0], b = w[1];
                __syncwarp();
                mw = hamax2(mw, stage_w(sm + SM_WA + j * 4096, tw >> 2, (tw & 3) * 2, a, b, (j & 2) ? 1.f : 0.5f));
            }
        }
        proxy_fence();
        asm volatile("bar.sync 8, %0;" ::"n"(NTA) : "memory");
        const uint32_t epoch = s_misc[7];
        if (hmag(mw) > H_MAX) s_misc[4] = 1;
        if (w4 == 0) {
            if (REDAT < 0 && (MODE & 1) && lane == 0) asm volatile("red.relaxed.gpu.global.add.u32 [%0], %1;" ::"l"(p.cnt), "r"(cta == 0 ? 1024 - G + 1 : 1) : "memory");
            if (MODE == 3) {
                if (lane == 0) wait_count(p.cnt, epoch << 10);
                __syncwarp();
                if (!HSM) asm volatile("bar.arrive 13, 128;" ::: "memory");
            }
            if ((MODE & 2) && lane == 0) {
                expect_tx(sb + SM_RDY + 16, G * CV * 16);
                bulk_load(sb + SM_ENT, p.cell + cta * G * CV, LND0, sb + SM_RDY + 16);
                bulk_load(sb + SM_LND1, p.cell + cta * G * CV + LND0 / 16, G * CV * 16 - LND0, sb + SM_RDY + 16);
            }
            PROFT(11, NT);
            if (MODE & 1) {
                asm volatile("bar.sync 10, %0;" ::"n"(NB10) : "memory");
                if (lane == 0) {
#pragma unroll 1
                    for (int b = 0; b < NWG; b++)
                        asm volatile("cp.async.bulk.tensor.2d.global.shared::cta.bulk_group [%0, {%2, %3}], [%1];"
                                     ::"l"(&hmap), "r"(sb + SM_RING + b * XROWS * 128), "r"(0), "r"(node0 + b * XROWS) : "memory");
                    asm volatile("cp.async.bulk.commit_group;" ::: "memory");
                    PROFT(12, NT);
                    asm volatile("cp.async.bulk.wait_group 0;" ::: "memory");
                    PROFT(13, NT);
                    if (MODE & 2) {
                        asm volatile("red.release.gpu.global.add.u32 [%0], %1;" ::"l"(p.cnt + 32), "r"(cta == 0 ? 1024 - G + 1 : 1) : "memory");
                        wait_count(p.cnt + 32, epoch << 10);
                    }
                    PROFT(15, NT);
                }
                __syncwarp();
            }
        } else if (MODE & 2) {
            const uint32_t tag5 = epoch << 27, tag23 = epoch << 9;
            const int t = tw - 32;
            const uint4* hp = p.cell + (cta * G + t) * CV;
            uint4 h[2] = {make_uint4(0, 0, 0, tag5), make_uint4(0, 0, 0, tag5)};
            if (HSM) {
                mbar_wait(sb + SM_RDY + 16);
                h[0] = *reinterpret_cast<const uint4*>(sm + (t * CV * 16 < LND0 ? SM_ENT : SM_LND1 - LND0) + t * CV * 16);
                static_assert(96 * CV * 16 >= LND0 || CV < 22, "landing");
                if (t < G - 96) h[1] = *reinterpret_cast<const uint4*>(sm + ((t + 96) * CV * 16 < LND0 ? SM_ENT : SM_LND1 - LND0) + (t + 96) * CV * 16);
            } else {
                if (MODE == 3) asm volatile("bar.sync 13, 128;" ::: "memory");
                ld_relaxed16_if(h[0], hp, true);
                ld_relaxed16_if(h[1], hp + 96 * CV, t < G - 96);
            }
#pragma unroll
            for (int r = 0; r < 2; r++) {
                for (uint32_t it = 0; (h[r].w ^ tag5) >= (1u << 27); it++) {
                    h[r] = ld_relaxed16(hp + r * 96 * CV);
                    spin_limit(it);
                }
                if (h[r].x > CAPC) s_misc[0] = 1;
                else if (h[r].x > 3 * CV) s_hist[atomicAdd(&s_misc[6], 1u)] = (t + 96 * r) | (h[r].x << 8);
            }
            asm volatile("bar.sync 12, 96;" ::: "memory");
            const uint32_t nl = s_misc[6], i = t % CX;
            for (uint32_t ev = t / CX, first = 1; first || ev - t / CX < nl; ev += 96 / CX, first = 0) {
                const uint32_t l = ev < nl && t < 96 / CX * CX ? s_hist[ev] : 0;
                const bool on = 3 * CV + i < (l >> 8);
                const uint2* ep = p.ext + (cta * G + (l & 0xff)) * CX + i;
                uint2 v;
                if (on) asm volatile("ld.relaxed.gpu.global.v2.u32 {%0,%1}, [%2];" : "=r"(v.x), "=r"(v.y) : "l"(ep) : "memory");
                if (MODE == 3 && HOLD && first) asm volatile("bar.arrive 10, %0;" ::"n"(NB10) : "memory");
                if (on) {
                    for (uint32_t it = 0; (v.y ^ tag23) > 0x1ff; it++) {
                        asm volatile("ld.relaxed.gpu.global.v2.u32 {%0,%1}, [%2];" : "=r"(v.x), "=r"(v.y) : "l"(ep) : "memory");
                        spin_limit(it);
                    }
                    atomicAdd(&s_deg[v.y & 0x1ff], 1u);
                    const uint32_t o = atomicAdd(&s_misc[1], 1u);
                    if (o < OVF_CAP) s_ovf[o] = make_uint2(v.x, v.y & 0x1ff); else s_misc[0] = 1;
                }
                __syncwarp();
            }
            asm volatile("bar.arrive 11, %0;" ::"n"(NT + 96) : "memory");
        }
        if (!(MODE & 2)) return;
        cta_bar();
        if (s_misc[5] | s_misc[4] | (s_misc[2] ^ 1)) return;
        const uint32_t step0 = s_misc[8 + w4];
        const int T = (s_misc[9 + w4] - step0 + NSTEP - 1) / NSTEP;
        const int q = lane >> 3, c8 = lane & 7;
        uint32_t pipe = sb + SM_PIPE + w4 * 32;
        uint32_t sidx = sb + SM_ENT + step0 * 32 + q * 8;
        uint32_t sd0 = sb + SM_RING + w4 * (2 * TB) + q * 256 + ((c8 ^ (2 * q)) << 4);
        uint32_t se = sb + SM_EXT + w4 * 256 + ((c8 ^ (2 * w4)) << 4) + q * 4;
        const uint32_t xlo = (uint32_t)reinterpret_cast<uint64_t>(p.x16) + c8 * 16;
        const uint32_t xhi = (uint32_t)(reinterpret_cast<uint64_t>(p.x16) >> 32);
#pragma unroll 1
        for (int i = 0; i < T; i++) {
            uint2 nx[NSTEP];
            const uint2 ee = lds64v(sidx + 32 * c8);
#pragma unroll
            for (int j = 0; j < NSTEP; j++) nx[j] = lds64v(sidx + 32 * j);
            const uint32_t e2 = __byte_perm(ee.x, ee.y, 0x7632);
            uint32_t pm;
            asm("set.nan.u32.f16x2 %0, %1, %1;" : "=r"(pm) : "r"(e2));
            if (!ONEBAR) mbar_wait(pipe + 16, ((i >> 1) & 1) ^ 1);
            else if (i > 0) {
                cp_wait<0>();
                if (FENCE) proxy_fence();
                asm volatile("bar.sync %0, 288;" ::"r"(1 + w4) : "memory");
            }
            asm volatile("st.shared.u32 [%0], %1;" ::"r"(se), "r"(e2 & ~pm) : "memory");
            asm volatile("st.shared.u32 [%0+128], %1;" ::"r"(se ^ 16), "r"(pm & 0x40004000u) : "memory");
#pragma unroll
            for (int u = 0; u < 2 * NSTEP; u++) {
                uint64_t ga;
                asm("{\n.reg .b32 lo;\ndp2a.lo.u32.u32 lo, %1, 0x80, %2;\nmov.b64 %0, {lo, %3};\n}"
                    : "=l"(ga) : "r"((u & 1) ? nx[u >> 1].y : nx[u >> 1].x), "r"(xlo), "r"(xhi));
                cp16((sd0 ^ ((u & 1) * 16)) + (u & 1) * 128 + (u >> 1) * 1024, reinterpret_cast<const void*>(ga));
            }
            cp_commit();
            sidx += TN * 4;
            sd0 ^= TB;
            se ^= 2048;
            if (!ONEBAR) {
                cp_wait<0>();
                if (FENCE) proxy_fence();
                __syncwarp();
                if (lane == 0) mbar_arrive(pipe);
                pipe ^= 8;
            }
        }
        if (ONEBAR) {
            cp_wait<0>();
            if (FENCE) proxy_fence();
            uint32_t tm = 0;
#pragma unroll
            for (int k = 0; k < NWG; k++) tm = max(tm, (s_misc[9 + k] - s_misc[8 + k] + NSTEP - 1) / NSTEP);
            for (uint32_t i = T - 1; i < tm + (w4 == 0); i++) asm volatile("bar.sync %0, 288;" ::"r"(1 + w4) : "memory");
        }
    } else {
        const uint32_t bar = sb + SM_BAR + wg * 24;
        const int e0 = cta * p.chunk + wg * VWG * 4;
        const int nvec = min(min(p.chunk - wg * VWG * 4, p.E - e0) >> 2, VWG);
        auto load_srce = [&]() {
            expect_tx(bar + 8, nvec * 24);
            bulk_stream(sb + SM_ENT + wg * VWG * 24, p.src + e0, nvec * 16, bar + 8);
            bulk_stream(sb + SM_ENT + wg * VWG * 24 + VWG * 16, p.e + e0, nvec * 8, bar + 8);
        };
        auto load_x = [&]() {
            if (tw == 0) {
                expect_tx(bar + 16, XROWS * 128);
                asm volatile("cp.async.bulk.tensor.2d.shared::cluster.global.mbarrier::complete_tx::bytes [%0], [%1, {%3, %4}], [%2];"
                             ::"r"(sb + SM_RING + wg * XROWS * 128), "l"(&xmap), "r"(bar + 16), "r"(0), "r"(node0 + wg * XROWS) : "memory");
            }
        };
        if (tw == 0) {
#pragma unroll
            for (int i = 0; i < 3; i++) asm volatile("mbarrier.init.shared::cta.b64 [%0], 1;" ::"r"(bar + i * 8) : "memory");
            proxy_fence();
            if (MODE & 1) {
                expect_tx(bar, nvec * 16);
                bulk_stream(sb + SM_RING + wg * XROWS * 128, p.dst + e0, nvec * 16, bar);
                if (!DELAY) load_srce();
            }
#pragma unroll
            for (int i = 0; i < 4; i++)
                asm volatile("mbarrier.init.shared::cta.b64 [%0], %1;" ::"r"(sb + SM_PIPE + wg * 32 + i * 8), "r"(i < 2 ? 1 : 4) : "memory");
        }
        if (MODE == 2) load_x();
        uint32_t cnt0;
        asm volatile("ld.relaxed.gpu.global.u32 %0, [%1];" : "=r"(cnt0) : "l"(p.cnt + opaque32(0)) : "memory");

        if (tid < (SM_HIST - SM_DEG) / 16) reinterpret_cast<uint4*>(sm + SM_DEG)[tid] = make_uint4(0, 0, 0, 0);
        if (tid < 144) s_hist[tid] = 1;
        if (tid < 512 - NSLOT) s_nb[NSLOT + tid] = 0x80000000u;
        if (tid < (NWG * GPW + 1) * 8) s_gi[tid] = make_uint2(sb + SM_TBL, xrow0);
        if (MODE & 1) {
            const uint32_t f = NSLOT + ((2 * tid) & 127);
#pragma unroll
            for (int j = 0; j < (G * CAPC / 2 + NT - 1) / NT; j++)
                if (tid + NT * j < G * CAPC / 2) reinterpret_cast<uint4*>(sm + SM_TBL)[tid + NT * j] = make_uint4(0, f, 0, f + 1);
            if (DELAY && tw == 0) load_srce();
        }
        edge_bar();

        const uint32_t epoch = (cnt0 >> 10) + (MODE == 2 ? 0 : 1);
        const uint32_t tag5 = epoch << 27, tag23 = epoch << 9;
        const int xb = tid / CV, xi = tid - xb * CV;
        if (MODE & 1) {
            int4 dv[VPT];
            mbar_wait(bar);
#pragma unroll
            for (int j = 0; j < VPT; j++) dv[j] = reinterpret_cast<const int4*>(sm + SM_RING + wg * XROWS * 128)[tw + 128 * j];
            PROF(1);
            uint32_t key[VPT * 4];
#pragma unroll
            for (int j = 0; j < VPT; j++) {
                const bool ok = tw + 128 * j < nvec;
                const int d[4] = {dv[j].x, dv[j].y, dv[j].z, dv[j].w};
#pragma unroll
                for (int q = 0; q < 4; q++) {
                    const uint32_t b = ok ? __umulhi((uint32_t)d[q], p.magic) : G;
                    const uint32_t r = atomicAdd(&s_hist[b], 1u);
                    key[j * 4 + q] = (b * CAPC + min(r, CAPC - 1u)) | ((uint32_t)(d[q] - b * p.npc) << 16);
                }
            }
            proxy_fence();
            wg_bar(1 + wg);
            PROF(2);
            mbar_wait(bar + 8);
            if (XPOS == 2) load_x();
            uint2* stage = reinterpret_cast<uint2*>(sm + SM_TBL);
            uint32_t emax = 0;
#pragma unroll
            for (int j = 0; j < VPT; j++) {
                const uint4 sv = reinterpret_cast<const uint4*>(sm + SM_ENT + wg * VWG * 24)[tw + 128 * j];
                uint2 ev = reinterpret_cast<const uint2*>(sm + SM_ENT + wg * VWG * 24 + VWG * 16)[tw + 128 * j];
                ev.x = bf2h(ev.x); ev.y = bf2h(ev.y);
                if (tw + 128 * j < nvec) emax = hamax2(emax, hamax2(ev.x, ev.y));
                const uint32_t w0[4] = {__byte_perm(sv.x, ev.x, 0x5410), __byte_perm(sv.y, ev.x, 0x7610),
                                        __byte_perm(sv.z, ev.y, 0x5410), __byte_perm(sv.w, ev.y, 0x7610)};
#pragma unroll
                for (int q = 0; q < 4; q++) stage[key[j * 4 + q] & 0xffff] = make_uint2(w0[q], key[j * 4 + q] >> 16);
            }
            if (hmag(emax) > H_MAX) s_misc[3] = 0x10000;
            if (XPOS == 3) load_x();
            edge_bar();
            if (XPOS == 4) load_x();
            PROF(3);
            uint32_t big = 0;
            if (tid < NXT) {
                const uint2* st = stage + xb * CAPC + xi * 3;
                uint4* gc = p.cell + (xb * G + cta) * CV + xi;
                uint4 v[RND];
#pragma unroll
                for (int j = 0; j < RND; j++)
                    if (xb + BPR * j < G) {
                        const uint2 a = st[j * BPR * CAPC], b = st[j * BPR * CAPC + 1], c = st[j * BPR * CAPC + 2];
                        v[j] = make_uint4(a.x, b.x, c.x, a.y + b.y * 512 + c.y * 262144 + tag5);
                        if (xi == 0) v[j].x = s_hist[xb + BPR * j] + s_misc[3];
                    }
#pragma unroll
                for (int j = 0; j < RND; j++)
                    if (xb + BPR * j < G) {
                        if (WEAK) gc[j * BPR * G * CV] = v[j]; else st_relaxed16(gc + j * BPR * G * CV, v[j]);
                        if (j == REDAT && tid == REDTH) asm volatile("red.relaxed.gpu.global.add.u32 [%0], %1;" ::"l"(p.cnt), "r"(cta == 0 ? 1024 - G + 1 : 1) : "memory");
                        big |= xi == 0 && v[j].x > 3 * CV ? 1u << j : 0u;
                    }
            }
            for (;;) {
                const uint32_t m = __ballot_sync(0xffffffffu, big != 0);
                if (!m) break;
                const int l = __ffs(m) - 1;
                const int b = __shfl_sync(0xffffffffu, xb + BPR * (__ffs(big) - 1), l);
                if (lane == l) big &= big - 1;
                if (lane < CX) {
                    const uint2 v = stage[b * CAPC + 3 * CV + lane];
                    asm volatile("st.relaxed.gpu.global.v2.u32 [%0], {%1,%2};" ::"l"(p.ext + (b * G + cta) * CX + lane), "r"(v.x), "r"(v.y | tag23) : "memory");
                }
            }
        }
        if (tid == 0) s_misc[7] = epoch;
        proxy_fence();
        asm volatile("bar.sync 8, %0;" ::"n"(NTA) : "memory");
        asm volatile("setmaxnreg.inc.sync.aligned.u32 112;");
        PROF(4);
        {
            mbar_wait(bar + 16);
            uint4* xs = reinterpret_cast<uint4*>(sm + SM_RING + wg * XROWS * 128) + tw;
            uint4 v[XROWS / 16];
            uint32_t mx = 0;
#pragma unroll
            for (int j = 0; j < XROWS / 16; j++) v[j] = xs[128 * j];
#pragma unroll
            for (int j = 0; j < XROWS / 16; j++) {
                v[j].x = bf2h(v[j].x); v[j].y = bf2h(v[j].y); v[j].z = bf2h(v[j].z); v[j].w = bf2h(v[j].w);
                xs[128 * j] = v[j];
                mx = hamax2(mx, hamax2(hamax2(v[j].x, v[j].y), hamax2(v[j].z, v[j].w)));
            }
            proxy_fence();
            if (MODE & 1) asm volatile("bar.arrive 10, %0;" ::"n"(NB10) : "memory");
            if (!(MODE & 2)) return;
            wg_bar(1 + wg);
            if (hmag(mx) > H_MAX) s_misc[4] = 1;
            if (hmag(mx) >= H_MIN) s_misc[2] = 1;
        }
        uint32_t da[24], du[24];
        {
            const uint32_t dx = (1u << 16) | ((sb + SM_RING + wg * XROWS * 128) >> 4);
            constexpr uint32_t dw = (1u << 16) | ((sb + SM_WA) >> 4);
            wg_fence();
            mma_ss<0>(da, dw, dx);
            mma_ss<0>(du, dw + 512, dx);
#pragma unroll
            for (int k = 1; k < 4; k++) { mma_ss<1>(da, dw + 128 * k, dx + 2 * k); mma_ss<1>(du, dw + 512 + 128 * k, dx + 2 * k); }
            wg_commit();
            wg_wait<0>();
            keep(da); keep(du);
        }
        auto table = [&]() {
            unsigned char* tb = sm + SM_TBL + (wg * XROWS + 2 * t4) * 256 + ((ch * 4) ^ (t4 << 5));
#pragma unroll
            for (int j = 0; j < 12; j++)
#pragma unroll
                for (int h = 0; h < 2; h++)
                    if (j < 11 || wg * XROWS + 8 * j + 2 * t4 + h < NROW)
                        *reinterpret_cast<uint2*>(tb + (8 * j + h) * 256) =
                            make_uint2(__byte_perm(da[2 * j], da[2 * j + 1], h ? 0x7632 : 0x5410), __byte_perm(du[2 * j], du[2 * j + 1], h ? 0x7632 : 0x5410));
        };
        if (wg < NWG - 1) table();
        PROF(5);
        uint4 en[RNC];
        const uint4* gc = p.cell + cta * G * CV + tid;
        const bool lastr = warp * 32 + (RNC - 1) * NT < G * CV;
        mbar_wait(sb + SM_RDY + 16);
#pragma unroll
        for (int j = 0; j < RNC; j++) {
            const bool on = j < RNC - 1 || tid + j * NT < G * CV;
            if (on) en[j] = reinterpret_cast<const uint4*>(sm + (j < 4 ? SM_ENT : SM_LND1 - LND0))[j * NT + tid];
            else en[j] = make_uint4(0, 0, 0, tag5 | ((NSLOT + lane) * 0x40201u));
        }
        for (uint32_t it = 0;; it++) {
            uint32_t miss = 0;
#pragma unroll
            for (int j = 0; j < RNC; j++) miss |= en[j].w ^ tag5;
            if (miss < (1u << 27)) break;
#pragma unroll
            for (int j = 0; j < RNC; j++)
                ld_relaxed16_if(en[j], gc + j * NT, (en[j].w ^ tag5) >= (1u << 27));
            spin_limit(it);
        }
        __syncwarp();
        PROF(6);
        uint32_t d4[RNC * 3];
#pragma unroll
        for (int j = 0; j < RNC; j++)
#pragma unroll
            for (int s = 0; s < 3; s++) d4[3 * j + s] = (s == 0 ? en[j].w << 2 : en[j].w >> (9 * s - 2)) & 0x7fc;
#pragma unroll
        for (int k = 0; k < RNC * 3 - 3; k++) asm volatile("red.shared.add.u32 [%0+%1], 1;" ::"r"(d4[k]), "n"(sb + SM_DEG) : "memory");
        if (lastr) {
#pragma unroll
            for (int k = RNC * 3 - 3; k < RNC * 3; k++) asm volatile("red.shared.add.u32 [%0+%1], 1;" ::"r"(d4[k]), "n"(sb + SM_DEG) : "memory");
        }
        asm volatile("bar.sync 11, %0;" ::"n"(NT + 96) : "memory");
        PROF(7);
        uint32_t pad0 = 0, pad1 = 0, unused = 0;
        if (warp < NSLOT / 32) {
            const uint32_t dg = s_deg[tid];
            if (dg > 62 || xrow0 > ~0u - NSLOT * 128 || (uint32_t)oa > ~0u - NSLOT * 128) s_misc[0] = 1;
            const uint32_t kb = tid < nvalid ? 62 - min(dg, 62u) : 63;
            const uint32_t r = atomicAdd(&s_dh[kb], 1u);
            node_bar();
            const uint2 h = reinterpret_cast<const uint2*>(s_dh)[lane];
            uint32_t inc = h.x + h.y;
#pragma unroll
            for (int o = 1; o < 32; o <<= 1) { const uint32_t v = __shfl_up_sync(0xffffffffu, inc, o); if (lane >= o) inc += v; }
            const uint32_t pe = __shfl_sync(0xffffffffu, inc - h.x - h.y, kb >> 1), po = __shfl_sync(0xffffffffu, inc - h.y, kb >> 1);
            const uint32_t pos = ((kb & 1) ? po : pe) + r;
            const uint32_t grp = pos >> 3, slot = pos & 7, row = grp / NWG, col = grp - row * NWG;
            const uint32_t seg = SNAKE == 0 ? ((row & 1) ? col : NWG - 1 - col) : SNAKE == 1 ? ((row & 1) ? NWG - 1 - col : col)
                                            : ((grp < 16 ? 0x1b1e1be4u : grp < 32 ? 0x1e391b2du : 0x1be42d39u) >> (2 * (grp & 15))) & 3;
            const uint32_t idx = seg * GPW + GPW - 1 - row;
            if (slot == 0) s_lg[idx] = max(dg, (uint32_t)NSTEP);
            node_bar();
            const uint2 l = reinterpret_cast<const uint2*>(s_lg)[lane];
            uint32_t in2 = l.x + l.y;
#pragma unroll
            for (int o = 1; o < 32; o <<= 1) { const uint32_t v = __shfl_up_sync(0xffffffffu, in2, o); if (lane >= o) in2 += v; }
            const uint32_t ex2 = in2 - l.x - l.y;
            const uint32_t mine = __shfl_sync(0xffffffffu, ex2, (lane / (GPW / 2)) * (GPW / 2));
            const uint32_t ee = __shfl_sync(0xffffffffu, in2 - l.y, idx >> 1), eo = __shfl_sync(0xffffffffu, in2, idx >> 1);
            const uint32_t sbeg = __shfl_sync(0xffffffffu, ex2, seg * (GPW / 2));
            if (__any_sync(0xffffffffu, in2 > CAP / 8 || in2 - mine > MAXT * NSTEP) || s_misc[0] != 0) {
                s_misc[5] = 1;
            } else {
                const uint32_t gend = (idx & 1) ? eo : ee;
                const uint32_t first = gend - dg;
                s_nb[tid] = first * 32 + slot * 4;
                if (tid < nvalid) s_gi[idx * 8 + slot] = make_uint2(sb + SM_TBL + tid * 256 + (((tid >> 1) & 3) << 5), xrow0 + tid * 128);
                else unused = (idx * 8 + slot) | ((seg * GPW + GPW - 1) * 8 + slot) << 16;
                if (slot == 0) {
                    const uint32_t last = gend - 1 - sbeg;
                    s_mask[seg * MAXT + last / NSTEP] = last % NSTEP + 1;
                }
                if (tid <= NWG * (GPW / 2) && tid % (GPW / 2) == 0) s_misc[8 + tid / (GPW / 2)] = ex2;
                pad0 = (gend - s_lg[idx]) * 8 + slot; pad1 = first * 8;
                const uint32_t tot = __shfl_sync(0xffffffffu, in2, 31);
                if (tid < TN) s_ent[tot * 8 + tid] = node0;
            }
        } else {
            table();
        }
        edge_bar();
        PROF(8);
        if (s_misc[5] == 0) {
            auto place = [&](int j0, int j1) {
#pragma unroll
                for (int k = 3 * j0; k < 3 * j1; k++)
                    asm volatile("atom.shared.add.u32 %0, [%0+%1], 32;" : "+r"(d4[k]) : "n"(sb + SM_NB) : "memory");
#pragma unroll
                for (int j = j0; j < j1; j++)
#pragma unroll
                    for (int s = 0; s < 3; s++)
                        asm volatile("{\n.reg .pred q;\nsetp.ge.s32 q, %0, 0;\n@q st.shared.u32 [%0+%2], %1;\n}"
                                     ::"r"(d4[3 * j + s]), "r"(s == 0 ? en[j].x : s == 1 ? en[j].y : en[j].z), "n"(sb + SM_ENT));
            };
            if (lastr) place(0, RNC); else place(0, RNC - 1);
            for (; pad0 < pad1; pad0 += 8) s_ent[pad0] = node0 | (tid < nvalid ? E_PAD : 0u);
            if (unused) { const uint2 v = s_gi[unused >> 16]; s_gi[unused & 0xffff] = make_uint2(v.x ^ 8, v.y); }
            if (tid < s_misc[1]) {
                const uint2 v = s_ovf[tid];
                s_ent[atomicAdd(&s_nb[v.y], 32u) >> 2] = v.x;
            }
        }
        cta_bar();
        PROF(9);
        uint32_t plain = s_misc[5] | s_misc[4] | (s_misc[2] ^ 1);
        if (!plain) {
        uint32_t fb[16], fv[16], fe[4];
        {
            const uint32_t a = sb + SM_WA + 16384 + ((lane >> 4) * 8 + (lane & 7)) * 128 + (((2 * w4 + ((lane >> 3) & 1)) ^ (lane & 7)) << 4);
#pragma unroll
            for (int k = 0; k < 4; k++) {
                ldsm_t(fb + 4 * k, a + k * 2048);
                ldsm_t(fv + 4 * k, a + 8192 + k * 2048);
            }
            const uint32_t wh = reinterpret_cast<const uint32_t*>(sm + SM_WC)[ch >> 1];
            fe[0] = t4 != wg ? 0 : __byte_perm(wh, 0xfb53, 0x5410);
            fe[1] = t4 != wg ? 0 : __byte_perm(wh, 0xfb53, 0x5432);
        }
        const uint32_t step0 = __shfl_sync(0xffffffffu, s_misc[8 + wg], 0), nstep = __shfl_sync(0xffffffffu, s_misc[9 + wg], 0) - step0;
        const int T = (nstep + NSTEP - 1) / NSTEP;
        uint32_t pipe = sb + SM_PIPE + wg * 32;
        uint32_t dx = (1u << 16) | ((sb + SM_RING + wg * (2 * TB)) >> 4);
        uint32_t de = (1u << 16) | ((sb + SM_EXT) >> 4);
        uint32_t ma = sb + SM_MASK + wg * MAXT * 4;

        uint32_t hN[2], hD[2], hA[2];
        uint32_t u2[2], x2[2], flags = 0, nmax = 0;
        uint32_t gptr = opaque32(sb + SM_GI + wg * GPW * 64 + t4 * 16);
        auto pin = [&](uint32_t v) { return __shfl_sync(0xffffffffu, v + lane, lane) - lane; };
        const uint32_t tb4 = pin(ch * 4), chx = pin(ch * 2), cho = pin(ch * 2 + (uint32_t)oa - xrow0);
        uint64_t px[2], po[2];
#pragma unroll
        for (int h = 0; h < 2; h++) {
            px[h] = (uint64_t)(pin((uint32_t)(xa >> 32) + h) - h) << 32;
            po[h] = (uint64_t)(pin((uint32_t)(oa >> 32) + h) - h) << 32;
        }
        auto set_lo = [&](uint64_t& a, uint32_t r, uint32_t c) {
            asm("{\n.reg .b32 lo, hi;\nmov.b64 {lo, hi}, %0;\nadd.u32 lo, %1, %2;\nmov.b64 %0, {lo, hi};\n}" : "+l"(a) : "r"(r), "r"(c));
        };
        auto init_group = [&]() {
            const uint4 gi = lds128(gptr);
            gptr += 64;
            const uint2 t0 = lds64(gi.x ^ tb4), t1 = lds64(gi.z ^ tb4);
            set_lo(px[0], gi.y, chx); set_lo(px[1], gi.w, chx);
            set_lo(po[0], gi.y, cho); set_lo(po[1], gi.w, cho);
            x2[0] = ldg32(reinterpret_cast<const void*>(px[0]));
            x2[1] = ldg32(reinterpret_cast<const void*>(px[1]));
            u2[0] = t0.y; u2[1] = t1.y;
            const uint32_t a0 = __byte_perm(t0.x, t1.x, 0x5410), a1 = __byte_perm(t0.x, t1.x, 0x7632);
            hA[0] = hsub2(a0, fe[2]); hA[1] = hsub2(a1, fe[3]);
            fe[2] = a0; fe[3] = a1;
            hN[0] = hN[1] = 0; hD[0] = hD[1] = DEN0;
        };
        auto flush_group = [&]() {
            const uint32_t o0 = finish2(h_lo(hN[0]), h_lo(hD[0]), h_lo(hN[1]), h_lo(hD[1]), u2[0], x2[0]);
            const uint32_t o1 = finish2(h_hi(hN[0]), h_hi(hD[0]), h_hi(hN[1]), h_hi(hD[1]), u2[1], x2[1]);
            asm volatile("st.global.u32 [%0], %1;" ::"l"(po[0]), "r"(o0) : "memory");
            asm volatile("st.global.u32 [%0], %1;" ::"l"(po[1]), "r"(o1) : "memory");
            nmax = hamax2(nmax, hamax2(hN[0], hN[1]));
            flags = (flags >> 1) | (~(__vminu2(hD[0], hD[1]) + (0x80008000u - DEN_SMALL)) & 0x80008000u);
        };
        uint32_t db[ACC], dv_[ACC];
        const float c256 = PINC ? __uint_as_float(pin(0x43800000u)) : 256.f;
        auto gate = [&](uint32_t g) { return pack_h(fmaf(tanh_(h_lo(g)), c256, 256.f), fmaf(tanh_(h_hi(g)), c256, 256.f)); };
        fe[2] = fe[3] = 0;
        init_group();
        const uint32_t tok = pin(1 + wg), tnx = pin(1 + ((wg + 1) & 3));
        if (TOKEN && wg == NWG - 1) asm volatile("bar.arrive 1, %0;" ::"n"(NTOK) : "memory");
        const uint32_t mend = ma + 4 * T;
#pragma unroll 1
        for (int i = 0; ONEBAR ? ma != mend : i < T; i++) {
            uint32_t m;
            asm volatile("ld.shared.u32 %0, [%1];" : "=r"(m) : "r"(ma));
            ma += 4;
            if (!ONEBAR) mbar_wait(pipe, (i >> 1) & 1);
            if (TOKEN) asm volatile("bar.sync %0, %1;" ::"r"(tok), "n"(NTOK) : "memory");
            wg_fence();
            if (AHEAD) {
                mma_rs<0, 0>(db, fb, dx, HI_SW);
#pragma unroll
                for (int k = 1; k < 4; k++) mma_rs<1, 0>(db, fb + 4 * k, dx + 2 * k, HI_SW);
                mma_rs<1, 1>(db, fe, de, HI_SW);
                wg_commit();
                mma_rs<0, 0>(dv_, fv, dx, HI_SW);
#pragma unroll
                for (int k = 1; k < 4; k++) mma_rs<1, 0>(dv_, fv + 4 * k, dx + 2 * k, HI_SW);
            } else {
                mma_rs<0, 0>(dv_, fv, dx, HI_SW);
                mma_rs<0, 0>(db, fb, dx, HI_SW);
#pragma unroll
                for (int k = 1; k < 4; k++) {
                    mma_rs<1, 0>(dv_, fv + 4 * k, dx + 2 * k, HI_SW);
                    mma_rs<1, 0>(db, fb + 4 * k, dx + 2 * k, HI_SW);
                }
                mma_rs<1, 1>(db, fe, de, HI_SW);
            }
            wg_commit();
            if (TOKEN) asm volatile("bar.arrive %0, %1;" ::"r"(tnx), "n"(NTOK) : "memory");
            dx ^= TB >> 4;
            de ^= 128;
            uint32_t wp[AHEAD ? 2 * AHEAD : 1];
            if (AHEAD) {
                wg_wait<1>();
                keep(db); keep(fe);
#pragma unroll
                for (int j = 0; j < 2 * AHEAD; j++) wp[j] = gate(db[j]);
                keep(wp);
            }
            auto block = [&](int e) {
                wg_wait<0>();
                keep(dv_);
                if (!AHEAD) { keep(db); keep(fe); }
                if (!ONEBAR) asm volatile("{\n.reg .pred q;\nelect.sync _|q, 0xffffffff;\n@q mbarrier.arrive.shared::cta.b64 _, [%0];\n}" ::"r"(pipe + 16) : "memory");
#pragma unroll
                for (int j = 0; j < NSTEP; j++) {
#pragma unroll
                    for (int r = 0; r < 2; r++) {
                        const uint32_t w = e > 0 && j >= e ? gate(hadd2(db[2 * j + r], hA[r])) : j < AHEAD ? wp[2 * j + r] : gate(db[2 * j + r]);
                        hD[r] = hadd2(hD[r], w);
                        hN[r] = hfma2(w, dv_[2 * j + r], hN[r]);
                    }
                    if (j + 1 == e) { flush_group(); init_group(); }
                }
            };
            if (m == 0) block(0);
            else if (m & 1) {
                if (m & 2) { if (m & 4) block(7); else block(3); } else { if (m & 4) block(5); else block(1); }
            } else {
                if (m & 2) { if (m & 4) block(6); else block(2); } else { if (m & 4) block(4); else block(8); }
            }
            pipe ^= 8;
        }
        PROF(10);
        if (TOKEN) {
            uint32_t tm = 0;
#pragma unroll
            for (int k = 0; k < NWG; k++) tm = max(tm, (s_misc[9 + k] - s_misc[8 + k] + NSTEP - 1) / NSTEP);
            for (uint32_t i = T; i < tm; i++) {
                asm volatile("bar.sync %0, %1;" ::"r"(tok), "n"(NTOK) : "memory");
                asm volatile("bar.arrive %0, %1;" ::"r"(tnx), "n"(NTOK) : "memory");
            }
            if (wg == 0) asm volatile("bar.sync 1, %0;" ::"n"(NTOK) : "memory");
        }
        if (__any_sync(0xffffffffu, flags != 0)) redo_small(p, sm, flags, wg);
        asm volatile("{\n.reg .pred q;\nsetp.ge.u32 q, %1, 0x7c00;\nbar.red.or.pred q, 9, %2, q;\nselp.u32 %0, 1, 0, q;\n}"
                     : "=r"(plain) : "r"(hmag(nmax)), "n"(NT) : "memory");
        }
        if (plain) slow_bin(p, sm, node0, nvalid);
        PROF(14);
    }
}

typedef CUresult (*EncodeFn)(CUtensorMap*, CUtensorMapDataType, cuuint32_t, void*, const cuuint64_t*, const cuuint64_t*,
                             const cuuint32_t*, const cuuint32_t*, CUtensorMapInterleave, CUtensorMapSwizzle,
                             CUtensorMapL2promotion, CUtensorMapFloatOOBfill);

}

extern "C" void kernel_launch(void* const* d_in, const int* in_sizes, int n_in, void* d_out, int out_size) {
    static int sms = 0;
    static EncodeFn encode = nullptr;
    static void *cell = nullptr, *ext = nullptr, *cnt = nullptr, *x16 = nullptr;
    if (!sms) {
        int dev = 0;
        cudaGetDevice(&dev);
        cudaDeviceGetAttribute(&sms, cudaDevAttrMultiProcessorCount, dev);
        cudaFuncSetAttribute(gatedgcn_kernel<1>, cudaFuncAttributeMaxDynamicSharedMemorySize, SM_TOTAL);
        cudaFuncSetAttribute(gatedgcn_kernel<2>, cudaFuncAttributeMaxDynamicSharedMemorySize, SM_TOTAL);
        cudaFuncSetAttribute(gatedgcn_kernel<3>, cudaFuncAttributeMaxDynamicSharedMemorySize, SM_TOTAL);
        cudaDriverEntryPointQueryResult qr;
        cudaGetDriverEntryPoint("cuTensorMapEncodeTiled", (void**)&encode, cudaEnableDefault, &qr);
        cudaGetSymbolAddress(&cell, g_cell);
        cudaGetSymbolAddress(&ext, g_ext);
        cudaGetSymbolAddress(&cnt, g_cnt);
        cudaGetSymbolAddress(&x16, g_x16);
        if (((uint64_t)x16 >> 32) != (((uint64_t)x16 + G * NSLOT * 128 - 1) >> 32)) x16 = (char*)x16 + G * NSLOT * 128;
    }
    Params p;
    p.x = (const __nv_bfloat16*)d_in[0];
    p.e = (const __nv_bfloat16*)d_in[1];
    p.src = (const int*)d_in[2];
    p.dst = (const int*)d_in[3];
    p.wa = (const __nv_bfloat16*)d_in[4];
    p.wb = (const __nv_bfloat16*)d_in[5];
    p.wc = (const __nv_bfloat16*)d_in[6];
    p.wu = (const __nv_bfloat16*)d_in[7];
    p.wv = (const __nv_bfloat16*)d_in[8];
    p.out = (__nv_bfloat16*)d_out;
    p.cell = (uint4*)cell;
    p.ext = (uint2*)ext;
    p.cnt = (uint32_t*)cnt;
    p.x16 = (const uint4*)x16;
    p.N = in_sizes[0] / 64;
    p.E = in_sizes[2];
    p.npc = (p.N + G - 1) / G;
    p.chunk = ((p.E + G - 1) / G + 7) & ~7;
    p.magic = (uint32_t)(0x100000000ull / (uint32_t)p.npc) + 1u;
    if (!encode || p.npc > NROW || p.N - (G - 1) * p.npc < 8 * NWG || p.chunk > CHUNK_MAX || (p.E & 7) ||
        p.E - (G - 1) * p.chunk <= (NWG - 1) * VWG * 4) return;

    CUtensorMap xmap, hmap;
    const cuuint64_t dims[2] = {64, (cuuint64_t)p.N};
    const cuuint64_t strides[1] = {128};
    const cuuint32_t box[2] = {64, XROWS}, estr[2] = {1, 1};
    encode(&xmap, CU_TENSOR_MAP_DATA_TYPE_BFLOAT16, 2, d_in[0], dims, strides, box, estr, CU_TENSOR_MAP_INTERLEAVE_NONE,
           CU_TENSOR_MAP_SWIZZLE_128B, CU_TENSOR_MAP_L2_PROMOTION_L2_256B, CU_TENSOR_MAP_FLOAT_OOB_FILL_NONE);
    encode(&hmap, CU_TENSOR_MAP_DATA_TYPE_FLOAT16, 2, x16, dims, strides, box, estr, CU_TENSOR_MAP_INTERLEAVE_NONE,
           CU_TENSOR_MAP_SWIZZLE_128B, CU_TENSOR_MAP_L2_PROMOTION_NONE, CU_TENSOR_MAP_FLOAT_OOB_FILL_NONE);
    if (sms >= G) {
        gatedgcn_kernel<3><<<G, NTA, SM_TOTAL>>>(p, xmap, hmap);
    } else {
        gatedgcn_kernel<1><<<G, NTA, SM_TOTAL>>>(p, xmap, hmap);
        gatedgcn_kernel<2><<<G, NTA, SM_TOTAL>>>(p, xmap, hmap);
    }
}
```

```cpp
#include <cuda_runtime.h>
#include <cuda_bf16.h>
#include <cuda_fp16.h>
#include <cuda.h>
#include <stdint.h>

namespace {

constexpr int G = 132;
constexpr int NWG = 4;
constexpr int NT = NWG * 128;
constexpr int NW = NT / 32;
constexpr int NTA = NT + 128;
constexpr int NSLOT = 384;
constexpr int NROW = 380;
constexpr int GPW = NSLOT / 8 / NWG;
constexpr int XROWS = NSLOT / NWG;
constexpr int VPT = 3;
constexpr int VWG = 128 * VPT;
constexpr int CHUNK_MAX = NT * VPT * 4;
constexpr int CV = 18;
constexpr int CX = 32;
constexpr int CAPC = 3 * CV + CX;
constexpr int LSTR = 160;
constexpr int BPR = NT / CV;
constexpr int RND = (G + BPR - 1) / BPR;
constexpr int RNC = (G * CV + NT - 1) / NT;
constexpr int TAILS = 192;
constexpr int NSTEP = 8;
constexpr int TB = NSTEP * 8 * 128;
constexpr int CAP = 6784;
constexpr int CAPX = CAP + NSTEP * 8;
constexpr int MAXT = 40;
static_assert(GPW % 2 == 0 && GPW <= 16 && G <= 192 && RNC == 5, "layout");

constexpr uint32_t SB = 1024;
constexpr int SM_RING = 0;
constexpr int SM_W = SM_RING + NSLOT * 128;
constexpr int SM_TBL = SM_W + 4 * 8192;
constexpr int SM_ENT = SM_TBL + NROW * 256;
constexpr int SM_EXT = SM_ENT + CHUNK_MAX * 6;
constexpr int SM_DEG = SM_EXT + 4096;
constexpr int SM_DH = SM_DEG + 512 * 4;
constexpr int SM_LG = SM_DH + 64 * 4;
constexpr int SM_END = SM_LG + 64 * 4;
constexpr int SM_MISC = SM_END + NWG * MAXT * 4;
constexpr int SM_HIST = SM_MISC + 64;
constexpr int SM_CUR = SM_HIST + 144 * 4;
constexpr int SM_GI = SM_CUR + 512 * 4;
constexpr int SM_TAIL = SM_GI + (NWG * GPW + 1) * 64;
constexpr int SM_BAR = SM_TAIL + TAILS * 4;
constexpr int SM_LBAR = SM_BAR + 96;
constexpr int SM_WC = SM_LBAR + 32;
constexpr int SM_TOTAL = SM_WC + 128;
constexpr int LND = 2 * NT * 16;
constexpr int SM_LND2 = SM_TBL + (NWG - 1) * XROWS * 256;
static_assert(SM_TOTAL <= 232448 && NSLOT * 128 * 4 <= SM_DEG, "smem");
static_assert(NWG * 2 * TB <= SM_W + 16384 && SM_TBL % 1024 == 0 && SM_EXT % 1024 == 0 && (SB + SM_EXT) % 4096 < 2048, "align");
static_assert((G + 1) * CAPC * 8 <= NROW * 256 && CAPC % 2 == 0, "outgoing cells");
static_assert(CAPX * 4 <= CHUNK_MAX * 6 && 2 * LND <= CHUNK_MAX * 6 && SM_LND2 + G * CV * 16 - 2 * LND <= SM_ENT, "aliases");
static_assert(SM_CUR % 16 == 0 && SM_GI % 16 == 0 && SM_WC % 16 == 0, "vector access");
enum { M_NOFIT, M_NTAIL, M_XBIG, M_XBAD, M_RANGE, M_SKIP, M_EPOCH, M_STEP0 = 8 };
enum { B_EDGE = 6, B_NODE, B_SENT, B_FINAL, B_CONV, B_COUNT, B_TAIL, B_READY, B_SORT };

__device__ __align__(128) uint4 g_cell[G * G * CV];
__device__ __align__(128) uint64_t g_ext[G * G * CX];
__device__ __align__(128) uint32_t g_len[G * LSTR];
__device__ __align__(128) uint4 g_x16[2 * G * NSLOT * 8];
__device__ __align__(128) uint32_t g_cnt[64];
#define PROFT(i, t)
#define PROF(i) PROFT(i, 0)

constexpr uint32_t DEN0 = 0x00220022u;
constexpr uint32_t DEN_SMALL = 0x03470347u;
constexpr uint32_t E_PAD = 0xffff0000u;
constexpr uint32_t H_MAX = 0x4ff0u;
constexpr uint32_t A_MAX = 0x5000u;
constexpr uint32_t SQ_MAX = 0x6380u;
constexpr uint32_t SQ_MIN = 0x2240u;

__device__ __forceinline__ float tanh_(float x) { float y; asm("tanh.approx.f32 %0, %1;" : "=f"(y) : "f"(x)); return y; }
__device__ __forceinline__ float rcp(float x) { float y; asm("rcp.approx.ftz.f32 %0, %1;" : "=f"(y) : "f"(x)); return y; }
__device__ __forceinline__ uint32_t pack_bf16(float lo, float hi) { uint32_t r; asm("cvt.rn.bf16x2.f32 %0, %1, %2;" : "=r"(r) : "f"(hi), "f"(lo)); return r; }
__device__ __forceinline__ uint32_t pack_h(float lo, float hi) { uint32_t r; asm("cvt.rn.f16x2.f32 %0, %1, %2;" : "=r"(r) : "f"(hi), "f"(lo)); return r; }
__device__ __forceinline__ float h_lo(uint32_t v) { return __low2float(*reinterpret_cast<__half2*>(&v)); }
__device__ __forceinline__ float h_hi(uint32_t v) { return __high2float(*reinterpret_cast<__half2*>(&v)); }
__device__ __forceinline__ uint32_t hadd2(uint32_t a, uint32_t b) { uint32_t r; asm("add.rn.f16x2 %0, %1, %2;" : "=r"(r) : "r"(a), "r"(b)); return r; }
__device__ __forceinline__ uint32_t hsub2(uint32_t a, uint32_t b) { uint32_t r; asm("sub.rn.f16x2 %0, %1, %2;" : "=r"(r) : "r"(a), "r"(b)); return r; }
__device__ __forceinline__ uint32_t hfma2(uint32_t a, uint32_t b, uint32_t c) { uint32_t r; asm("fma.rn.f16x2 %0, %1, %2, %3;" : "=r"(r) : "r"(a), "r"(b), "r"(c)); return r; }
__device__ __forceinline__ uint32_t hamax2(uint32_t a, uint32_t b) { uint32_t r; asm("max.NaN.xorsign.abs.f16x2 %0, %1, %2;" : "=r"(r) : "r"(a), "r"(b)); return r; }
__device__ __forceinline__ uint32_t hmag(uint32_t m) { return max(m & 0x7fffu, (m >> 16) & 0x7fffu); }
__device__ __forceinline__ float bf_lo(uint32_t v) { return __uint_as_float(v << 16); }
__device__ __forceinline__ float bf_hi(uint32_t v) { return __uint_as_float(v & 0xffff0000u); }
__device__ __forceinline__ uint32_t bf2h(uint32_t v) { return pack_h(bf_lo(v), bf_hi(v)); }
__device__ __forceinline__ uint32_t finish2(float n0, float r0, float n1, float r1, uint32_t u, uint32_t x) {
    uint32_t z, o;
    asm("cvt.rn.relu.bf16x2.f32 %0, %1, %2;" : "=r"(z) : "f"(fmaf(n1, r1, h_hi(u))), "f"(fmaf(n0, r0, h_lo(u))));
    asm("add.rn.bf16x2 %0, %1, %2;" : "=r"(o) : "r"(z), "r"(x));
    return o;
}
__device__ __forceinline__ uint32_t opaque32(uint32_t v) { asm volatile("" : "+r"(v)); return v; }
__device__ __forceinline__ uint2 lds64(uint32_t a) { uint2 v; asm volatile("ld.shared.v2.u32 {%0,%1}, [%2];" : "=r"(v.x), "=r"(v.y) : "r"(a)); return v; }
__device__ __forceinline__ uint4 lds128(uint32_t a) {
    uint4 v;
    asm("ld.shared.v4.u32 {%0,%1,%2,%3}, [%4];" : "=r"(v.x), "=r"(v.y), "=r"(v.z), "=r"(v.w) : "r"(a));
    return v;
}
__device__ __forceinline__ uint32_t ldg32(const void* p) { uint32_t v; asm("ld.global.nc.u32 %0, [%1];" : "=r"(v) : "l"(p)); return v; }

__device__ __forceinline__ void spin_limit(uint32_t it) {
    asm volatile("{\n.reg .pred q;\n.reg .b64 z;\nmov.b64 z, 0;\nsetp.gt.u32 q, %0, 0x400000;\n@q st.global.u32 [z], %0;\n}" ::"r"(it));
}
__device__ __forceinline__ void wg_fence() { asm volatile("wgmma.fence.sync.aligned;" ::: "memory"); }
__device__ __forceinline__ void wg_commit() { asm volatile("wgmma.commit_group.sync.aligned;" ::: "memory"); }
__device__ __forceinline__ void wg_wait() { asm volatile("wgmma.wait_group.sync.aligned 0;" ::: "memory"); }
__device__ __forceinline__ void proxy_fence() { asm volatile("fence.proxy.async.shared::cta;" ::: "memory"); }
__device__ __forceinline__ void cp_commit() { asm volatile("cp.async.commit_group;" ::: "memory"); }
__device__ __forceinline__ void cp_wait() { asm volatile("cp.async.wait_group 0;" ::: "memory"); }
__device__ __forceinline__ void cp16(uint32_t dst, const void* src) { asm volatile("cp.async.cg.shared.global [%0], [%1], 16;" ::"r"(dst), "l"(src) : "memory"); }
template <int ID, int N> __device__ __forceinline__ void bar_sync() { asm volatile("bar.sync %0, %1;" ::"n"(ID), "n"(N) : "memory"); }
template <int ID, int N> __device__ __forceinline__ void bar_arrive() { asm volatile("bar.arrive %0, %1;" ::"n"(ID), "n"(N) : "memory"); }
template <int N> __device__ __forceinline__ void bar_sync(uint32_t id) { asm volatile("bar.sync %0, %1;" ::"r"(id), "n"(N) : "memory"); }
template <int N> __device__ __forceinline__ void bar_arrive(uint32_t id) { asm volatile("bar.arrive %0, %1;" ::"r"(id), "n"(N) : "memory"); }
__device__ __forceinline__ uint32_t ld_relaxed(const uint32_t* p) {
    uint32_t v;
    asm volatile("ld.relaxed.gpu.global.u32 %0, [%1];" : "=r"(v) : "l"(p) : "memory");
    return v;
}
__device__ __forceinline__ void st_relaxed(uint32_t* p, uint32_t v) { asm volatile("st.relaxed.gpu.global.u32 [%0], %1;" ::"l"(p), "r"(v) : "memory"); }
__device__ __forceinline__ uint2 ld_relaxed8(const void* p) {
    uint2 v;
    asm volatile("{\n.reg .b64 t;\nld.relaxed.gpu.global.b64 t, [%2];\nmov.b64 {%0, %1}, t;\n}" : "=r"(v.x), "=r"(v.y) : "l"(p) : "memory");
    return v;
}
__device__ __forceinline__ void st_relaxed8(void* p, uint32_t lo, uint32_t hi) {
    asm volatile("{\n.reg .b64 t;\nmov.b64 t, {%1, %2};\nst.relaxed.gpu.global.b64 [%0], t;\n}" ::"l"(p), "r"(lo), "r"(hi) : "memory");
}
__device__ __forceinline__ void bulk_load(uint32_t dst, const void* src, uint32_t bytes, uint32_t bar) {
    asm volatile("cp.async.bulk.shared::cluster.global.mbarrier::complete_tx::bytes [%0], [%1], %2, [%3];"
                 ::"r"(dst), "l"(src), "r"(bytes), "r"(bar) : "memory");
}
__device__ __forceinline__ void mbar_init(uint32_t bar) { asm volatile("mbarrier.init.shared::cta.b64 [%0], 1;" ::"r"(bar) : "memory"); }
__device__ __forceinline__ void expect_tx(uint32_t bar, uint32_t bytes) {
    asm volatile("mbarrier.arrive.expect_tx.shared::cta.b64 _, [%0], %1;" ::"r"(bar), "r"(bytes) : "memory");
}
__device__ __forceinline__ bool mbar_try(uint32_t bar) {
    uint32_t ok;
    asm volatile("{\n.reg .pred q;\nmbarrier.try_wait.parity.shared::cta.b64 q, [%1], 0;\nselp.u32 %0, 1, 0, q;\n}"
                 : "=r"(ok) : "r"(bar) : "memory");
    return ok;
}
__device__ __forceinline__ void mbar_wait(uint32_t bar) {
    for (uint32_t it = 0; !mbar_try(bar); it++) spin_limit(it);
}
__device__ __forceinline__ void ld_relaxed16_if(uint4& v, const uint4* p, bool on) {
    asm volatile("{\n.reg .pred q;\n.reg .b128 t;\n.reg .b64 a, b;\nsetp.ne.u32 q, %5, 0;\n"
                 "mov.b64 a, {%0, %1};\nmov.b64 b, {%2, %3};\nmov.b128 t, {a, b};\n@q ld.relaxed.gpu.global.b128 t, [%4];\n"
                 "mov.b128 {a, b}, t;\nmov.b64 {%0, %1}, a;\nmov.b64 {%2, %3}, b;\n}"
                 : "+r"(v.x), "+r"(v.y), "+r"(v.z), "+r"(v.w) : "l"(p), "r"((uint32_t)on) : "memory");
}
__device__ __forceinline__ void st_relaxed16(uint4* p, uint4 v) {
    asm volatile("{\n.reg .b128 t;\n.reg .b64 a, b;\nmov.b64 a, {%1, %2};\nmov.b64 b, {%3, %4};\nmov.b128 t, {a, b};\n"
                 "st.relaxed.gpu.global.b128 [%0], t;\n}"
                 ::"l"(p), "r"(v.x), "r"(v.y), "r"(v.z), "r"(v.w) : "memory");
}

#define R4(d, o) "+r"(d[o]), "+r"(d[o + 1]), "+r"(d[o + 2]), "+r"(d[o + 3])
#define L16 "%0,%1,%2,%3,%4,%5,%6,%7,%8,%9,%10,%11,%12,%13,%14,%15"
#define L24 L16 ",%16,%17,%18,%19,%20,%21,%22,%23"
constexpr uint32_t HI_SW = 0x40000000u | 64u;
template <int A>
__device__ __forceinline__ void mma_ss(uint32_t (&d)[24], uint32_t alo, uint32_t blo) {
    asm volatile("{\n.reg .b64 a, b;\nmov.b64 a, {%24, %26};\nmov.b64 b, {%25, %26};\n"
                 "wgmma.mma_async.sync.aligned.m64n96k16.f16.f16.f16 {" L24 "}, a, b, %27, 1, 1, 1, 0;\n}\n"
                 : R4(d, 0), R4(d, 4), R4(d, 8), R4(d, 12), R4(d, 16), R4(d, 20)
                 : "r"(alo), "r"(blo), "r"(HI_SW), "n"(A));
}
template <int A, int T>
__device__ __forceinline__ void mma_rs(uint32_t (&d)[16], const uint32_t* a, uint32_t blo) {
    asm volatile("{\n.reg .b64 b;\nmov.b64 b, {%20, %21};\n"
                 "wgmma.mma_async.sync.aligned.m64n64k16.f16.f16.f16 {" L16 "}, {%16,%17,%18,%19}, b, %22, 1, 1, %23;\n}\n"
                 : R4(d, 0), R4(d, 4), R4(d, 8), R4(d, 12)
                 : "r"(a[0]), "r"(a[1]), "r"(a[2]), "r"(a[3]), "r"(blo), "r"(HI_SW), "n"(A), "n"(T));
}
template <int R> __device__ __forceinline__ void keep(uint32_t (&d)[R]) {
#pragma unroll
    for (int i = 0; i < R; i++) asm volatile("" : "+r"(d[i])::"memory");
}
__device__ __forceinline__ void ldsm_t(uint32_t* f, uint32_t addr) {
    asm volatile("ldmatrix.sync.aligned.m8n8.x4.trans.shared.b16 {%0,%1,%2,%3}, [%4];"
                 : "=r"(f[0]), "=r"(f[1]), "=r"(f[2]), "=r"(f[3]) : "r"(addr) : "memory");
}
__device__ __forceinline__ uint32_t stage_w(unsigned char* mat, int k, int c, uint4 a, uint4 b, float s) {
    unsigned char* row = mat + k * 128;
    const uint4 e = make_uint4(pack_h(s * bf_lo(a.x), s * bf_lo(a.y)), pack_h(s * bf_lo(a.z), s * bf_lo(a.w)),
                               pack_h(s * bf_lo(b.x), s * bf_lo(b.y)), pack_h(s * bf_lo(b.z), s * bf_lo(b.w)));
    const uint4 o = make_uint4(pack_h(s * bf_hi(a.x), s * bf_hi(a.y)), pack_h(s * bf_hi(a.z), s * bf_hi(a.w)),
                               pack_h(s * bf_hi(b.x), s * bf_hi(b.y)), pack_h(s * bf_hi(b.z), s * bf_hi(b.w)));
    *reinterpret_cast<uint4*>(row + ((c ^ (k & 7)) << 4)) = e;
    *reinterpret_cast<uint4*>(row + (((c + 1) ^ (k & 7)) << 4)) = o;
    return hamax2(hamax2(hamax2(e.x, e.y), hamax2(e.z, e.w)), hamax2(hamax2(o.x, o.y), hamax2(o.z, o.w)));
}

struct Params {
    const __nv_bfloat16* x;
    const __nv_bfloat16* e;
    const int* src;
    const int* dst;
    const __nv_bfloat16 *wa, *wb, *wc, *wu, *wv;
    __nv_bfloat16* out;
    uint4* cell;
    uint64_t* ext;
    uint32_t* len;
    uint32_t* cnt;
    const uint4* x16;
    int N, E, npc, chunk;
    uint32_t magic;
};

__device__ __noinline__ void slow_bin(const Params& p, unsigned char* sm, int node0, int nvalid) {
    float* acc = reinterpret_cast<float*>(sm);
    const int tid = threadIdx.x, lane = tid & 31, warp = tid >> 5;
    bar_sync<B_EDGE, NT>();
    for (int i = tid; i < NSLOT * 128; i += NT) acc[i] = 0.f;
    bar_sync<B_EDGE, NT>();
    const uint32_t* x2 = reinterpret_cast<const uint32_t*>(p.x);
    const uint32_t* wb = reinterpret_cast<const uint32_t*>(p.wb) + lane;
    const uint32_t* wv = reinterpret_cast<const uint32_t*>(p.wv) + lane;
    const uint32_t* wa = reinterpret_cast<const uint32_t*>(p.wa) + lane;
    const uint32_t* wu = reinterpret_cast<const uint32_t*>(p.wu) + lane;
    const uint32_t wc = reinterpret_cast<const uint32_t*>(p.wc)[lane];
    for (int i0 = warp * 32; i0 < p.E; i0 += NT) {
        const int dl = i0 + lane < p.E ? p.dst[i0 + lane] - node0 : -1;
        uint32_t m = __ballot_sync(0xffffffffu, (uint32_t)dl < (uint32_t)nvalid);
        while (m) {
            const int l = __ffs(m) - 1;
            m &= m - 1;
            const int d = __shfl_sync(0xffffffffu, dl, l);
            const uint32_t xs = x2[p.src[i0 + l] * 32 + lane], xd = x2[(node0 + d) * 32 + lane];
            float g0 = 0.f, g1 = 0.f, v0 = 0.f, v1 = 0.f;
#pragma unroll 4
            for (int k = 0; k < 32; k++) {
                const uint32_t a = __shfl_sync(0xffffffffu, xs, k), b = __shfl_sync(0xffffffffu, xd, k);
#pragma unroll
                for (int h = 0; h < 2; h++) {
                    const float fs = h ? bf_hi(a) : bf_lo(a), fd = h ? bf_hi(b) : bf_lo(b);
                    const uint32_t ua = wa[(2 * k + h) * 32], ub = wb[(2 * k + h) * 32], uv = wv[(2 * k + h) * 32];
                    g0 += fd * bf_lo(ua) + fs * bf_lo(ub);
                    g1 += fd * bf_hi(ua) + fs * bf_hi(ub);
                    v0 += fs * bf_lo(uv);
                    v1 += fs * bf_hi(uv);
                }
            }
            const float ev = __bfloat162float(p.e[i0 + l]);
            const float e0 = rcp(1.f + __expf(-(g0 + ev * bf_lo(wc))));
            const float e1 = rcp(1.f + __expf(-(g1 + ev * bf_hi(wc))));
            float* a = acc + d * 128 + 2 * lane;
            atomicAdd(a, e0);
            atomicAdd(a + 1, e1);
            atomicAdd(a + 64, e0 * v0);
            atomicAdd(a + 65, e1 * v1);
        }
    }
    bar_sync<B_EDGE, NT>();
    for (int n = warp; n < nvalid; n += NW) {
        const uint32_t xd = x2[(node0 + n) * 32 + lane];
        float u0 = 0.f, u1 = 0.f;
#pragma unroll 4
        for (int k = 0; k < 32; k++) {
            const uint32_t b = __shfl_sync(0xffffffffu, xd, k);
            const uint32_t w0 = wu[(2 * k) * 32], w1 = wu[(2 * k + 1) * 32];
            u0 += bf_lo(b) * bf_lo(w0) + bf_hi(b) * bf_lo(w1);
            u1 += bf_lo(b) * bf_hi(w0) + bf_hi(b) * bf_hi(w1);
        }
        const float* a = acc + n * 128 + 2 * lane;
        const float z0 = u0 + a[64] * rcp(a[0] + 1e-6f), z1 = u1 + a[65] * rcp(a[1] + 1e-6f);
        const float r0 = z0 > 0.f ? z0 : 0.f * z0, r1 = z1 > 0.f ? z1 : 0.f * z1;
        reinterpret_cast<uint32_t*>(p.out)[(node0 + n) * 32 + lane] = pack_bf16(bf_lo(xd) + r0, bf_hi(xd) + r1);
    }
}

__device__ __noinline__ void redo_small(const Params& p, const unsigned char* sm, uint32_t flags, int wg) {
    const int lane = threadIdx.x & 31, q = lane & 7;
    for (;;) {
        const uint32_t m = __ballot_sync(0xffffffffu, flags != 0);
        if (!m) break;
        const int l = __ffs(m) - 1;
        const uint32_t k = __ffs(__shfl_sync(0xffffffffu, flags, l)) - 1;
        if (lane == l) flags &= flags - 1;
        const uint2 gi = reinterpret_cast<const uint2*>(sm + SM_GI)[(wg * GPW + (k & 15) - (16 - GPW)) * 8 + 2 * (l & 3) + (k >> 4)];
        if (gi.x & 8) continue;
        const uint32_t pr = ((threadIdx.x >> 5) & 3) * 8 + (l >> 2);
        const uint32_t n = (gi.x - SB - SM_TBL) >> 8, row = blockIdx.x * p.npc + n;
        const uint32_t deg = reinterpret_cast<const uint32_t*>(sm + SM_DEG)[n];
        const uint32_t base = (reinterpret_cast<const uint32_t*>(sm + SM_CUR)[n] >> 2) - 8 * deg;
        const uint2 t = lds64(gi.x ^ (pr * 8));
        uint32_t wb[8], wv[8];
#pragma unroll
        for (int i = 0; i < 8; i++) {
            wb[i] = ldg32(reinterpret_cast<const uint32_t*>(p.wb) + (8 * q + i) * 32 + pr);
            wv[i] = ldg32(reinterpret_cast<const uint32_t*>(p.wv) + (8 * q + i) * 32 + pr);
        }
        const uint32_t wc = ldg32(reinterpret_cast<const uint32_t*>(p.wc) + pr);
        const uint32_t x = ldg32(reinterpret_cast<const uint32_t*>(p.x) + row * 32 + pr);
        float d0 = 0.f, d1 = 0.f, n0 = 0.f, n1 = 0.f;
        for (uint32_t i0 = 0; i0 < deg; i0 += 16) {
            uint4 xr[4];
            float ev[4];
#pragma unroll
            for (int u = 0; u < 4; u++) {
                const uint32_t i = min(i0 + 4 * u + (lane >> 3), deg - 1);
                const uint32_t en = reinterpret_cast<const uint32_t*>(sm + SM_ENT)[base + 8 * i];
                ev[u] = h_hi(en);
                xr[u] = __ldg(reinterpret_cast<const uint4*>(p.x) + (en & 0xffff) * 8 + q);
            }
#pragma unroll
            for (int u = 0; u < 4; u++) {
                const uint32_t xw[4] = {xr[u].x, xr[u].y, xr[u].z, xr[u].w};
                float b0 = 0.f, b1 = 0.f, v0 = 0.f, v1 = 0.f;
#pragma unroll
                for (int j = 0; j < 8; j++) {
                    const float f = (j & 1) ? bf_hi(xw[j >> 1]) : bf_lo(xw[j >> 1]);
                    b0 += f * bf_lo(wb[j]); b1 += f * bf_hi(wb[j]);
                    v0 += f * bf_lo(wv[j]); v1 += f * bf_hi(wv[j]);
                }
#pragma unroll
                for (int o = 1; o < 8; o <<= 1) {
                    b0 += __shfl_xor_sync(0xffffffffu, b0, o); b1 += __shfl_xor_sync(0xffffffffu, b1, o);
                    v0 += __shfl_xor_sync(0xffffffffu, v0, o); v1 += __shfl_xor_sync(0xffffffffu, v1, o);
                }
                const float on = i0 + 4 * u + (lane >> 3) < deg ? 1.f : 0.f;
                const float e0 = __fdividef(on, 1.f + __expf(-(2.f * h_lo(t.x) + b0 + ev[u] * bf_lo(wc))));
                const float e1 = __fdividef(on, 1.f + __expf(-(2.f * h_hi(t.x) + b1 + ev[u] * bf_hi(wc))));
                d0 += e0; d1 += e1; n0 += e0 * v0; n1 += e1 * v1;
            }
        }
#pragma unroll
        for (int o = 8; o < 32; o <<= 1) {
            d0 += __shfl_xor_sync(0xffffffffu, d0, o); d1 += __shfl_xor_sync(0xffffffffu, d1, o);
            n0 += __shfl_xor_sync(0xffffffffu, n0, o); n1 += __shfl_xor_sync(0xffffffffu, n1, o);
        }
        if (lane == l)
            reinterpret_cast<uint32_t*>(p.out)[row * 32 + pr] = finish2(n0, rcp(d0 + 1e-6f), n1, rcp(d1 + 1e-6f), t.y, x);
    }
}

template <int MODE>
__global__ void __launch_bounds__(NTA, 1) gatedgcn_kernel(const __grid_constant__ Params p, const __grid_constant__ CUtensorMap xmap,
                                                          const __grid_constant__ CUtensorMap hmap) {
    extern __shared__ __align__(1024) unsigned char sm[];
    constexpr uint32_t sb = SB;
    spin_limit((uint32_t)__cvta_generic_to_shared(sm) != SB ? ~0u : 0u);
    const int tid = threadIdx.x, lane = tid & 31;
    const int warp = __shfl_sync(0xffffffffu, tid >> 5, 0);
    const int wg = warp >> 2, w4 = warp & 3, g8 = lane >> 2, t4 = lane & 3, tw = tid & 127;
    const int cta = blockIdx.x;
    const int node0 = cta * p.npc;
    const int nvalid = min(p.npc, p.N - node0);
    const int ch = 16 * w4 + 2 * g8;
    const uint64_t xa = reinterpret_cast<uint64_t>(p.x) + (uint64_t)node0 * 128, oa = reinterpret_cast<uint64_t>(p.out) + (uint64_t)node0 * 128;
    const uint32_t xrow0 = (uint32_t)xa;

    const uint32_t share = cta == 0 ? 1024 - G + 1 : 1;

    uint32_t* s_hist = reinterpret_cast<uint32_t*>(sm + SM_HIST);
    uint32_t* s_deg = reinterpret_cast<uint32_t*>(sm + SM_DEG);
    uint32_t* s_cur = reinterpret_cast<uint32_t*>(sm + SM_CUR);
    uint2* s_gi = reinterpret_cast<uint2*>(sm + SM_GI);
    uint32_t* s_dh = reinterpret_cast<uint32_t*>(sm + SM_DH);
    uint32_t* s_lg = reinterpret_cast<uint32_t*>(sm + SM_LG);
    uint32_t* s_end = reinterpret_cast<uint32_t*>(sm + SM_END);
    uint32_t* s_tail = reinterpret_cast<uint32_t*>(sm + SM_TAIL);
    uint32_t* s_misc = reinterpret_cast<uint32_t*>(sm + SM_MISC);
    uint32_t* s_ent = reinterpret_cast<uint32_t*>(sm + SM_ENT);
    auto max_tiles = [&]() {
        uint32_t tm = 0;
#pragma unroll
        for (int k = 0; k < NWG; k++) tm = max(tm, (s_misc[M_STEP0 + 1 + k] - s_misc[M_STEP0 + k] + NSTEP - 1) / NSTEP);
        return tm;
    };

    PROF(0);
    if (wg == NWG) {
        if (tw == 0) {
#pragma unroll
            for (int i = 0; i < 4; i++) mbar_init(sb + SM_LBAR + 8 * i);
            proxy_fence();
            if (MODE & 2) {
                expect_tx(sb + SM_LBAR + 24, 4 * 8192 + 128);
                bulk_load(sb + SM_W, p.wa, 8192, sb + SM_LBAR + 24);
                bulk_load(sb + SM_W + 8192, p.wu, 8192, sb + SM_LBAR + 24);
                bulk_load(sb + SM_W + 16384, p.wb, 8192, sb + SM_LBAR + 24);
                bulk_load(sb + SM_W + 24576, p.wv, 8192, sb + SM_LBAR + 24);
                bulk_load(sb + SM_WC, p.wc, 128, sb + SM_LBAR + 24);
            }
        }
        asm volatile("setmaxnreg.dec.sync.aligned.u32 32;");
        uint32_t mw = 0;
        if (MODE & 2) {
            {
                const int k = (tw >> 3) & 7;
                const uint32_t one = tw >= 64 ? 0x3c00u << (16 * (k & 1)) : 0u;
                const uint4 v = make_uint4(k >> 1 == 0 ? one : 0, k >> 1 == 1 ? one : 0, k >> 1 == 2 ? one : 0, k >> 1 == 3 ? one : 0);
                reinterpret_cast<uint4*>(sm + SM_EXT)[tw] = v;
                reinterpret_cast<uint4*>(sm + SM_EXT)[tw + 128] = v;
            }
            bar_sync<1 + NWG, 128>();
            mbar_wait(sb + SM_LBAR + 24);
            if (w4 == 0) {
                mw = reinterpret_cast<uint32_t*>(sm + SM_WC)[lane];
                mw = pack_h(0.5f * bf_lo(mw), 0.5f * bf_hi(mw));
                reinterpret_cast<uint32_t*>(sm + SM_WC)[lane] = mw;
                mw = hmag(mw);
            }
#pragma unroll 1
            for (int j = 0; j < 8; j++) {
                const uint4* w = reinterpret_cast<const uint4*>(sm + SM_W + j * 4096) + tw * 2;
                const uint4 a = w[0], b = w[1];
                __syncwarp();
                const uint32_t m = hmag(stage_w(sm + SM_W + j * 4096, tw >> 2, (tw & 3) * 2, a, b, j >= 6 ? 256.f : (j & 2) ? 1.f : 0.5f));
                mw = max((int)mw, (int)m - (j >= 6 ? 8 << 10 : 0));
            }
        }
        proxy_fence();
        bar_sync<B_SENT, NTA>();
        const uint32_t epoch = s_misc[M_EPOCH];
        if (mw > H_MAX) s_misc[M_RANGE] = 1;
        if (w4 == 0) {
            if (MODE == 3) {
                if (lane == 0) for (uint32_t it = 0; ld_relaxed(p.cnt) != epoch << 10; it++) spin_limit(it);
                __syncwarp();
                bar_arrive<B_READY, 128>();
            }
            if ((MODE & 2) && lane == 0) {
                const uint4* in = p.cell + cta * G * CV;
                proxy_fence();
                expect_tx(sb + SM_LBAR, LND);
                bulk_load(sb + SM_ENT, in, LND, sb + SM_LBAR);
                expect_tx(sb + SM_LBAR + 8, LND);
                bulk_load(sb + SM_ENT + LND, in + LND / 16, LND, sb + SM_LBAR + 8);
                expect_tx(sb + SM_LBAR + 16, G * CV * 16 - 2 * LND);
                bulk_load(sb + SM_LND2, in + LND / 8, G * CV * 16 - 2 * LND, sb + SM_LBAR + 16);
            }
            PROFT(11, NT);
            if (MODE & 1) bar_sync<B_CONV, NT + 32>();
            if (lane == 0) {
                if (MODE & 1) {
#pragma unroll 1
                    for (int b = 0; b < NWG; b++)
                        asm volatile("cp.async.bulk.tensor.2d.global.shared::cta.bulk_group [%0, {%2, %3}], [%1];"
                                     ::"l"(&hmap), "r"(sb + SM_RING + b * XROWS * 128), "r"(0), "r"(node0 + b * XROWS) : "memory");
                    asm volatile("cp.async.bulk.commit_group;" ::: "memory");
                    PROFT(12, NT);
                    if (s_misc[M_XBAD]) st_relaxed(p.cnt + 33, epoch);
                    asm volatile("cp.async.bulk.wait_group 0;" ::: "memory");
                    PROFT(13, NT);
                    asm volatile("red.release.gpu.global.add.u32 [%0], %1;" ::"l"(p.cnt + 32), "r"(share) : "memory");
                }
                if (MODE & 2) {
                    uint2 c = ld_relaxed8(p.cnt + 32);
                    for (uint32_t it = 0; c.x != epoch << 10; it++) { c = ld_relaxed8(p.cnt + 32); spin_limit(it); }
                    asm volatile("fence.acquire.gpu;" ::: "memory");
                    if (c.y == epoch) s_misc[M_RANGE] = 1;
                }
                PROFT(15, NT);
            }
            __syncwarp();
        } else if (MODE & 2) {
            const uint32_t tag23 = epoch << 9;
            const int t = tw - 32;
            uint32_t ln[2] = {~tag23, t < G - 96 ? ~tag23 : tag23};
            for (uint32_t it = 0; ((ln[0] ^ tag23) | (ln[1] ^ tag23)) > 0x1ff; it++) {
#pragma unroll
                for (int r = 0; r < 2; r++)
                    if ((ln[r] ^ tag23) > 0x1ff) ln[r] = ld_relaxed(p.len + cta * LSTR + t + 96 * r);
                spin_limit(it);
            }
#pragma unroll
            for (int r = 0; r < 2; r++) {
                const int n = (int)(ln[r] & 0x1ff) - 3 * CV;
                if (n > 0) {
                    const uint32_t o = atomicAdd(&s_misc[M_NTAIL], n);
                    if (n > CX || o + n > TAILS) s_misc[M_NOFIT] = 1;
                    else for (int k = 0; k < n; k++) s_tail[o + k] = (t + 96 * r) * CX + k;
                }
            }
            bar_sync<B_TAIL, 96>();
            const uint32_t nt = s_misc[M_NOFIT] ? 0 : s_misc[M_NTAIL];
            const uint64_t* ep[2];
            uint2 v[2];
#pragma unroll
            for (int r = 0; r < 2; r++) {
                ep[r] = p.ext + cta * G * CX + (t + 96 * r < nt ? s_tail[t + 96 * r] : 0);
                v[r] = make_uint2(0, t + 96 * r < nt ? ~tag23 : tag23 | 511);
            }
            PROFT(1, NT + 32);
            if (MODE == 3) bar_sync<B_READY, 128>();
            for (uint32_t it = 0; ((v[0].y ^ tag23) | (v[1].y ^ tag23)) > 0x1ff; it++) {
#pragma unroll
                for (int r = 0; r < 2; r++)
                    if ((v[r].y ^ tag23) > 0x1ff) v[r] = ld_relaxed8(ep[r]);
                spin_limit(it);
            }
            atomicAdd(&s_deg[v[0].y & 0x1ff], 1u);
            atomicAdd(&s_deg[v[1].y & 0x1ff], 1u);
            PROFT(2, NT + 32);
            bar_sync<B_COUNT, NT + 96>();
            const uint32_t pv = node0 | E_PAD;
            for (int k = t; k < CAPX / 4; k += 96) reinterpret_cast<uint4*>(s_ent)[k] = make_uint4(pv, pv, pv, pv);
            bar_sync<B_SORT, NT + 96>();
            if (s_misc[M_SKIP] == 0) {
#pragma unroll
                for (int r = 0; r < 2; r++)
                    if (t + 96 * r < nt) s_ent[atomicAdd(&s_cur[v[r].y & 0x1ff], 32u) >> 2] = v[r].x;
            }
        }
        if (!(MODE & 2)) return;
        __syncthreads();
        if (s_misc[M_SKIP] | s_misc[M_RANGE] | (s_misc[M_XBIG] ^ 1)) return;
        const uint32_t step0 = s_misc[M_STEP0 + w4];
        const int T = (s_misc[M_STEP0 + 1 + w4] - step0 + NSTEP - 1) / NSTEP;
        const int q = lane >> 3, c8 = lane & 7;
        uint32_t sidx = sb + SM_ENT + step0 * 32 + q * 8;
        uint32_t sd0 = sb + SM_RING + w4 * (2 * TB) + q * 256 + ((c8 ^ (2 * q)) << 4);
        uint32_t se = sb + SM_EXT + w4 * 256 + ((c8 ^ (2 * w4)) << 4) + q * 4;
        const uint32_t xlo = (uint32_t)reinterpret_cast<uint64_t>(p.x16) + c8 * 16;
        const uint32_t xhi = (uint32_t)(reinterpret_cast<uint64_t>(p.x16) >> 32);
#pragma unroll 1
        for (int i = 0; i < T; i++) {
            uint2 nx[NSTEP];
            const uint2 ee = lds64(sidx + 32 * c8);
#pragma unroll
            for (int j = 0; j < NSTEP; j++) nx[j] = lds64(sidx + 32 * j);
            const uint32_t e2 = __byte_perm(ee.x, ee.y, 0x7632);
            uint32_t pm;
            asm("set.nan.u32.f16x2 %0, %1, %1;" : "=r"(pm) : "r"(e2));
            if (i > 0) {
                cp_wait();
                proxy_fence();
                bar_sync<288>(1 + w4);
            }
            asm volatile("st.shared.u32 [%0], %1;" ::"r"(se), "r"(e2 & ~pm) : "memory");
            asm volatile("st.shared.u32 [%0+128], %1;" ::"r"(se ^ 16), "r"(pm & 0x40004000u) : "memory");
#pragma unroll
            for (int u = 0; u < 2 * NSTEP; u++) {
                uint64_t ga;
                asm("{\n.reg .b32 lo;\ndp2a.lo.u32.u32 lo, %1, 0x80, %2;\nmov.b64 %0, {lo, %3};\n}"
                    : "=l"(ga) : "r"((u & 1) ? nx[u >> 1].y : nx[u >> 1].x), "r"(xlo), "r"(xhi));
                cp16((sd0 ^ ((u & 1) * 16)) + (u & 1) * 128 + (u >> 1) * 1024, reinterpret_cast<const void*>(ga));
            }
            cp_commit();
            sidx += NSTEP * 32;
            sd0 ^= TB;
            se ^= 2048;
        }
        cp_wait();
        proxy_fence();
        for (uint32_t i = T - 1, n = max_tiles() + (w4 == 0); i < n; i++) bar_sync<288>(1 + w4);
    } else {
        const uint32_t bar = sb + SM_BAR + wg * 24;
        const int e0 = cta * p.chunk + wg * VWG * 4;
        const int nvec = min(min(p.chunk - wg * VWG * 4, p.E - e0) >> 2, VWG);
        auto load_x = [&]() {
            if (tw == 0) {
                expect_tx(bar + 16, XROWS * 128);
                asm volatile("cp.async.bulk.tensor.2d.shared::cluster.global.mbarrier::complete_tx::bytes [%0], [%1, {%3, %4}], [%2];"
                             ::"r"(sb + SM_RING + wg * XROWS * 128), "l"(&xmap), "r"(bar + 16), "r"(0), "r"(node0 + wg * XROWS) : "memory");
            }
        };
        if (tw == 0) {
#pragma unroll
            for (int i = 0; i < 3; i++) mbar_init(bar + i * 8);
            proxy_fence();
            if (MODE & 1) {
                expect_tx(bar, nvec * 16);
                bulk_load(sb + SM_RING + wg * XROWS * 128, p.dst + e0, nvec * 16, bar);
            }
        }
        if (MODE == 2) load_x();
        const uint32_t cnt0 = ld_relaxed(p.cnt + opaque32(0));

        if (tid < (SM_CUR - SM_DEG) / 16) reinterpret_cast<uint4*>(sm + SM_DEG)[tid] = make_uint4(0, 0, 0, 0);
        if (tid < 32) s_cur[NSLOT + tid] = 0x80000000u;
        if (tid < 8) s_gi[NWG * GPW * 8 + tid] = make_uint2(sb + SM_TBL, xrow0);
        if (MODE & 1) {
#pragma unroll
            for (int j = 0; j < (G * CAPC / 2 + NT - 1) / NT; j++)
                if (tid + NT * j < G * CAPC / 2) reinterpret_cast<uint4*>(sm + SM_TBL)[tid + NT * j] = make_uint4(0, 511, 0, 511);
            if (tw == 0) {
                expect_tx(bar + 8, nvec * 24);
                bulk_load(sb + SM_ENT + wg * VWG * 24, p.src + e0, nvec * 16, bar + 8);
                bulk_load(sb + SM_ENT + wg * VWG * 24 + VWG * 16, p.e + e0, nvec * 8, bar + 8);
            }
        }
        bar_sync<B_EDGE, NT>();

        const uint32_t epoch = (cnt0 >> 10) + (MODE == 2 ? 0 : 1);
        const uint32_t tag5 = epoch << 27, tag23 = epoch << 9;
        if (MODE & 1) {
            int4 dv[VPT];
            mbar_wait(bar);
#pragma unroll
            for (int j = 0; j < VPT; j++) dv[j] = reinterpret_cast<const int4*>(sm + SM_RING + wg * XROWS * 128)[tw + 128 * j];
            uint32_t key[VPT * 4];
#pragma unroll
            for (int j = 0; j < VPT; j++) {
                const bool ok = tw + 128 * j < nvec;
                const int d[4] = {dv[j].x, dv[j].y, dv[j].z, dv[j].w};
#pragma unroll
                for (int q = 0; q < 4; q++) {
                    const uint32_t b = ok ? __umulhi((uint32_t)d[q], p.magic) : G;
                    const uint32_t r = atomicAdd(&s_hist[b], 1u);
                    key[j * 4 + q] = (b * CAPC + min(r, CAPC - 1u)) | ((uint32_t)(d[q] - b * p.npc) << 16);
                }
            }
            proxy_fence();
            bar_sync<B_EDGE, NT>();
            if (tid < G) {
                st_relaxed(p.len + tid * LSTR + cta, min(s_hist[tid], 511u) | tag23);
                if (cta < (-G & 7)) p.len[tid * LSTR + G + cta] = 0;
            }
            mbar_wait(bar + 8);
            load_x();
            uint2* stage = reinterpret_cast<uint2*>(sm + SM_TBL);
            uint32_t emax = 0;
#pragma unroll
            for (int j = 0; j < VPT; j++) {
                const uint4 sv = reinterpret_cast<const uint4*>(sm + SM_ENT + wg * VWG * 24)[tw + 128 * j];
                uint2 ev = reinterpret_cast<const uint2*>(sm + SM_ENT + wg * VWG * 24 + VWG * 16)[tw + 128 * j];
                ev.x = bf2h(ev.x); ev.y = bf2h(ev.y);
                if (tw + 128 * j < nvec) emax = hamax2(emax, hamax2(ev.x, ev.y));
                const uint32_t w0[4] = {__byte_perm(sv.x, ev.x, 0x5410), __byte_perm(sv.y, ev.x, 0x7610),
                                        __byte_perm(sv.z, ev.y, 0x5410), __byte_perm(sv.w, ev.y, 0x7610)};
#pragma unroll
                for (int q = 0; q < 4; q++) stage[key[j * 4 + q] & 0xffff] = make_uint2(w0[q], key[j * 4 + q] >> 16);
            }
            if (hmag(emax) > H_MAX) {
#pragma unroll
                for (int k = 0; k < VPT * 4; k++) stage[key[k] & 0xffff].y = 510;
            }
            bar_sync<B_EDGE, NT>();
            PROF(3);
            {
                const int b = warp + NW * lane;
                const uint32_t c = b < G ? s_hist[b] : 0;
                for (uint32_t m = __ballot_sync(0xffffffffu, c > 3 * CV); m; m &= m - 1) {
                    const int l = __ffs(m) - 1, bl = warp + NW * l;
                    if (3 * CV + (lane & ~3) < __shfl_sync(0xffffffffu, c, l)) {
                        const uint2 v = stage[bl * CAPC + 3 * CV + lane];
                        st_relaxed8(p.ext + (bl * G + cta) * CX + lane, v.x, v.y | tag23);
                    }
                }
            }
            if (tid < BPR * CV) {
                const int xb = tid / CV, xi = tid - xb * CV;
                const uint2* st = stage + xb * CAPC + xi * 3;
                uint4* gc = p.cell + (xb * G + cta) * CV + xi;
                uint4 v[RND];
#pragma unroll
                for (int j = 0; j < RND; j++)
                    if (xb + BPR * j < G) {
                        const uint2 a = st[j * BPR * CAPC], b = st[j * BPR * CAPC + 1], c = st[j * BPR * CAPC + 2];
                        v[j] = make_uint4(a.x, b.x, c.x, a.y + b.y * 512 + c.y * 262144 + tag5);
                    }
#pragma unroll
                for (int j = 0; j < RND; j++)
                    if (xb + BPR * j < G) {
                        st_relaxed16(gc + j * BPR * G * CV, v[j]);
                        if (j == 2 && tid == NT - 32) asm volatile("red.relaxed.gpu.global.add.u32 [%0], %1;" ::"l"(p.cnt), "r"(share) : "memory");
                    }
            }
        }
        if (tid == 0) s_misc[M_EPOCH] = epoch;
        bar_sync<B_SENT, NTA>();
        asm volatile("setmaxnreg.inc.sync.aligned.u32 112;");
        PROF(4);
        {
            mbar_wait(bar + 16);
            uint4* xs = reinterpret_cast<uint4*>(sm + SM_RING + wg * XROWS * 128) + tw;
            uint4 v[XROWS / 16];
            uint32_t mx = 0, my = 0;
#pragma unroll
            for (int j = 0; j < XROWS / 16; j++) v[j] = xs[128 * j];
#pragma unroll
            for (int j = 0; j < XROWS / 16; j++) {
                v[j].x = bf2h(v[j].x); v[j].y = bf2h(v[j].y); v[j].z = bf2h(v[j].z); v[j].w = bf2h(v[j].w);
                xs[128 * j] = v[j];
                mx = hfma2(v[j].x, v[j].x, hfma2(v[j].z, v[j].z, mx));
                my = hfma2(v[j].y, v[j].y, hfma2(v[j].w, v[j].w, my));
            }
            if (hmag(hamax2(mx, my)) > SQ_MAX) s_misc[M_XBAD] = 1;
            if (hmag(hamax2(mx, my)) >= SQ_MIN) s_misc[M_XBIG] = 1;
            proxy_fence();
            if (MODE & 1) bar_arrive<B_CONV, NT + 32>();
            if (!(MODE & 2)) return;
            bar_sync<128>(1 + wg);
        }
        uint32_t da[24], du[24];
        {
            const uint32_t dx = (1u << 16) | ((sb + SM_RING + wg * XROWS * 128) >> 4);
            constexpr uint32_t dw = (1u << 16) | ((sb + SM_W) >> 4);
            wg_fence();
            mma_ss<0>(da, dw, dx);
            mma_ss<0>(du, dw + 512, dx);
#pragma unroll
            for (int k = 1; k < 4; k++) { mma_ss<1>(da, dw + 128 * k, dx + 2 * k); mma_ss<1>(du, dw + 512 + 128 * k, dx + 2 * k); }
            wg_commit();
            wg_wait();
            keep(da); keep(du);
        }
        auto table = [&]() {
            unsigned char* tb = sm + SM_TBL + (wg * XROWS + 2 * t4) * 256 + ((ch * 4) ^ (t4 << 5));
            uint32_t am = 0;
#pragma unroll
            for (int j = 0; j < 12; j++) {
                am = hamax2(am, hamax2(da[2 * j], da[2 * j + 1]));
#pragma unroll
                for (int h = 0; h < 2; h++)
                    if (j < 11 || wg * XROWS + 8 * j + 2 * t4 + h < NROW)
                        *reinterpret_cast<uint2*>(tb + (8 * j + h) * 256) =
                            make_uint2(__byte_perm(da[2 * j], da[2 * j + 1], h ? 0x7632 : 0x5410), __byte_perm(du[2 * j], du[2 * j + 1], h ? 0x7632 : 0x5410));
            }
            if (hmag(am) > A_MAX) s_misc[M_RANGE] = 1;
        };
        if (wg < NWG - 1) table();
        PROF(5);
        uint4 en[RNC];
        uint32_t d4[RNC * 3];
        auto count = [&](int j0, int j1) {
            mbar_wait(sb + SM_LBAR + 4 * j0);
#pragma unroll
            for (int j = j0; j < j1; j++) {
                if (j < RNC - 1 || tid + j * NT < G * CV) en[j] = reinterpret_cast<const uint4*>(sm + (j < 4 ? SM_ENT : SM_LND2 - 2 * LND))[j * NT + tid];
                else en[j] = make_uint4(0, 0, 0, tag5 | 0x7ffffffu);
            }
            for (uint32_t it = 0;; it++) {
                uint32_t miss = 0;
#pragma unroll
                for (int j = j0; j < j1; j++) miss |= en[j].w ^ tag5;
                if (miss < (1u << 27)) break;
#pragma unroll
                for (int j = j0; j < j1; j++)
                    ld_relaxed16_if(en[j], p.cell + cta * G * CV + tid + j * NT, (en[j].w ^ tag5) >= (1u << 27));
                spin_limit(it);
            }
            __syncwarp();
#pragma unroll
            for (int j = j0; j < j1; j++)
#pragma unroll
                for (int s = 0; s < 3; s++) {
                    d4[3 * j + s] = (s == 0 ? en[j].w << 2 : en[j].w >> (9 * s - 2)) & 0x7fc;
                    asm volatile("red.shared.add.u32 [%0+%1], 1;" ::"r"(d4[3 * j + s]), "n"(sb + SM_DEG) : "memory");
                }
        };
        count(0, 2);
        count(2, 4);
        PROF(6);
        count(4, RNC);
        bar_sync<B_COUNT, NT + 96>();
        PROF(7);
        uint32_t unused = 0;
        if (warp < NSLOT / 32) {
            const uint32_t dg = s_deg[tid];
            if (dg > 62 || s_deg[510] || xrow0 > ~0u - NSLOT * 128 || (uint32_t)oa > ~0u - NSLOT * 128) s_misc[M_NOFIT] = 1;
            const uint32_t kb = tid < nvalid ? 62 - min(dg, 62u) : 63;
            const uint32_t r = atomicAdd(&s_dh[kb], 1u);
            bar_sync<B_NODE, NSLOT>();
            const uint2 h = reinterpret_cast<const uint2*>(s_dh)[lane];
            uint32_t inc = h.x + h.y;
#pragma unroll
            for (int o = 1; o < 32; o <<= 1) { const uint32_t v = __shfl_up_sync(0xffffffffu, inc, o); if (lane >= o) inc += v; }
            const uint32_t pe = __shfl_sync(0xffffffffu, inc - h.x - h.y, kb >> 1), po = __shfl_sync(0xffffffffu, inc - h.y, kb >> 1);
            const uint32_t pos = ((kb & 1) ? po : pe) + r;
            const uint32_t grp = pos >> 3, slot = pos & 7, row = grp / NWG, col = grp - row * NWG;
            const uint32_t seg = (row & 1) ? NWG - 1 - col : col;
            const uint32_t idx = seg * GPW + GPW - 1 - row;
            if (slot == 0) s_lg[idx] = max(dg, (uint32_t)NSTEP);
            bar_sync<B_NODE, NSLOT>();
            const uint2 l = reinterpret_cast<const uint2*>(s_lg)[lane];
            uint32_t in2 = l.x + l.y;
#pragma unroll
            for (int o = 1; o < 32; o <<= 1) { const uint32_t v = __shfl_up_sync(0xffffffffu, in2, o); if (lane >= o) in2 += v; }
            const uint32_t ex2 = in2 - l.x - l.y;
            const uint32_t mine = __shfl_sync(0xffffffffu, ex2, (lane / (GPW / 2)) * (GPW / 2));
            const uint32_t ee = __shfl_sync(0xffffffffu, in2 - l.y, idx >> 1), eo = __shfl_sync(0xffffffffu, in2, idx >> 1);
            const uint32_t sbeg = __shfl_sync(0xffffffffu, ex2, seg * (GPW / 2));
            if (__any_sync(0xffffffffu, in2 > CAP / 8 || in2 - mine > MAXT * NSTEP) || s_misc[M_NOFIT] != 0) {
                s_misc[M_SKIP] = 1;
            } else {
                const uint32_t gend = (idx & 1) ? eo : ee;
                s_cur[tid] = (gend - dg) * 32 + slot * 4;
                if (tid < nvalid) s_gi[idx * 8 + slot] = make_uint2(sb + SM_TBL + tid * 256 + (((tid >> 1) & 3) << 5), xrow0 + tid * 128);
                else unused = (idx * 8 + slot) | ((seg * GPW + GPW - 1) * 8 + slot) << 16;
                if (slot == 0) {
                    const uint32_t last = gend - 1 - sbeg;
                    s_end[seg * MAXT + last / NSTEP] = last % NSTEP + 1;
                }
                if (tid <= NWG * (GPW / 2) && tid % (GPW / 2) == 0) s_misc[M_STEP0 + tid / (GPW / 2)] = ex2;
            }
        } else {
            table();
        }
        bar_sync<B_SORT, NT + 96>();
        PROF(8);
        if (s_misc[M_SKIP] == 0) {
            if (unused) { const uint2 v = s_gi[unused >> 16]; s_gi[unused & 0xffff] = make_uint2(v.x ^ 8, v.y); }
            auto place = [&](int j1) {
#pragma unroll
                for (int k = 0; k < 3 * j1; k++)
                    asm volatile("atom.shared.add.u32 %0, [%1+%2], 32;" : "=r"(d4[k]) : "r"(min(d4[k], (NSLOT + lane) * 4u)), "n"(sb + SM_CUR) : "memory");
#pragma unroll
                for (int j = 0; j < j1; j++)
#pragma unroll
                    for (int s = 0; s < 3; s++)
                        asm volatile("{\n.reg .pred q;\nsetp.ge.s32 q, %0, 0;\n@q st.shared.u32 [%0+%2], %1;\n}"
                                     ::"r"(d4[3 * j + s]), "r"(s == 0 ? en[j].x : s == 1 ? en[j].y : en[j].z), "n"(sb + SM_ENT));
            };
            if (warp * 32 + (RNC - 1) * NT < G * CV) place(RNC); else place(RNC - 1);
        }
        __syncthreads();
        PROF(9);
        uint32_t plain = s_misc[M_SKIP] | s_misc[M_RANGE] | (s_misc[M_XBIG] ^ 1);
        if (!plain) {
            uint32_t fb[16], fv[16], fe[4];
            {
                const uint32_t a = sb + SM_W + 16384 + ((lane >> 4) * 8 + (lane & 7)) * 128 + (((2 * w4 + ((lane >> 3) & 1)) ^ (lane & 7)) << 4);
#pragma unroll
                for (int k = 0; k < 4; k++) {
                    ldsm_t(fb + 4 * k, a + k * 2048);
                    ldsm_t(fv + 4 * k, a + 8192 + k * 2048);
                }
                const uint32_t wh = reinterpret_cast<const uint32_t*>(sm + SM_WC)[ch >> 1];
                fe[0] = t4 != wg ? 0 : __byte_perm(wh, 0xfb53, 0x5410);
                fe[1] = t4 != wg ? 0 : __byte_perm(wh, 0xfb53, 0x5432);
                fe[2] = fe[3] = 0;
            }
            const uint32_t step0 = __shfl_sync(0xffffffffu, s_misc[M_STEP0 + wg], 0);
            const uint32_t T = (__shfl_sync(0xffffffffu, s_misc[M_STEP0 + 1 + wg], 0) - step0 + NSTEP - 1) / NSTEP;
            uint32_t dx = (1u << 16) | ((sb + SM_RING + wg * (2 * TB)) >> 4);
            uint32_t de = (1u << 16) | ((sb + SM_EXT) >> 4);
            uint32_t ma = sb + SM_END + wg * MAXT * 4;
            uint32_t gptr = opaque32(sb + SM_GI + wg * GPW * 64 + t4 * 16);
            auto pin = [&](uint32_t v) { return __shfl_sync(0xffffffffu, v + lane, lane) - lane; };
            const uint32_t tb4 = pin(ch * 4), chx = pin(ch * 2), cho = pin(ch * 2 + (uint32_t)oa - xrow0);
            uint64_t px[2], po[2];
#pragma unroll
            for (int h = 0; h < 2; h++) {
                px[h] = (uint64_t)(pin((uint32_t)(xa >> 32) + h) - h) << 32;
                po[h] = (uint64_t)(pin((uint32_t)(oa >> 32) + h) - h) << 32;
            }
            const uint32_t turn = pin(1 + wg), next = pin(1 + ((wg + 1) & 3));
            uint32_t flags = 0;
#pragma unroll 1
            for (int row = GPW - 1; (row + 1) * NWG * 8 > nvalid; row--) {
                const int pos = (row * NWG + ((row & 1) ? NWG - 1 - wg : wg)) * 8 + 2 * t4;
                flags |= ((pos + 1 >= nvalid ? 1u : 0u) | (pos >= nvalid ? 0x10000u : 0u)) << (GPW - 1 - row);
            }
            auto set_lo = [&](uint64_t& a, uint32_t r, uint32_t c) {
                asm("{\n.reg .b32 lo, hi;\nmov.b64 {lo, hi}, %0;\nadd.u32 lo, %1, %2;\nmov.b64 %0, {lo, hi};\n}" : "+l"(a) : "r"(r), "r"(c));
            };
            uint32_t hN[2], hD[2], hA[2], u2[2], x2[2], nmax = 0;
            uint4 gi;
            uint2 t0, t1;
            auto fetch_group = [&]() {
                gi = lds128(gptr);
                gptr += 64;
                t0 = lds64(gi.x ^ tb4); t1 = lds64(gi.z ^ tb4);
            };
            auto init_group = [&]() {
                set_lo(px[0], gi.y, chx); set_lo(px[1], gi.w, chx);
                set_lo(po[0], gi.y, cho); set_lo(po[1], gi.w, cho);
                x2[0] = ldg32(reinterpret_cast<const void*>(px[0]));
                x2[1] = ldg32(reinterpret_cast<const void*>(px[1]));
                u2[0] = t0.y; u2[1] = t1.y;
                const uint32_t a0 = __byte_perm(t0.x, t1.x, 0x5410), a1 = __byte_perm(t0.x, t1.x, 0x7632);
                hA[0] = hsub2(a0, fe[2]); hA[1] = hsub2(a1, fe[3]);
                fe[2] = a0; fe[3] = a1;
                hN[0] = hN[1] = 0; hD[0] = hD[1] = DEN0;
            };
            auto flush_group = [&]() {
                const float d0 = h_lo(hD[0]), d1 = h_lo(hD[1]), d2 = h_hi(hD[0]), d3 = h_hi(hD[1]);
                const float r0 = rcp(256.f * d0 * d1), r1 = rcp(256.f * d2 * d3);
                const uint32_t o0 = finish2(h_lo(hN[0]) * d1, r0, h_lo(hN[1]) * d0, r0, u2[0], x2[0]);
                const uint32_t o1 = finish2(h_hi(hN[0]) * d3, r1, h_hi(hN[1]) * d2, r1, u2[1], x2[1]);
                asm volatile("st.global.u32 [%0], %1;" ::"l"(po[0]), "r"(o0) : "memory");
                asm volatile("st.global.u32 [%0], %1;" ::"l"(po[1]), "r"(o1) : "memory");
                nmax = hamax2(nmax, hamax2(hN[0], hN[1]));
                flags = __funnelshift_r(flags, flags, 1) ^ (~(__vminu2(hD[0], hD[1]) + (0x80008000u - DEN_SMALL)) & 0x80008000u);
            };
            auto gate = [&](uint32_t g) { return pack_h(1.f + tanh_(h_lo(g)), 1.f + tanh_(h_hi(g))); };
            uint32_t db[2 * NSTEP], dv[2 * NSTEP];
            fetch_group();
            init_group();
            if (wg == NWG - 1) bar_arrive<1, 288>();
            const uint32_t mend = ma + 4 * T;
#pragma unroll 1
            while (ma != mend) {
                uint32_t m;
                asm volatile("ld.shared.u32 %0, [%1];" : "=r"(m) : "r"(ma));
                ma += 4;
                bar_sync<288>(turn);
                wg_fence();
                mma_rs<0, 0>(dv, fv, dx);
                mma_rs<0, 0>(db, fb, dx);
#pragma unroll
                for (int k = 1; k < 4; k++) {
                    mma_rs<1, 0>(dv, fv + 4 * k, dx + 2 * k);
                    mma_rs<1, 0>(db, fb + 4 * k, dx + 2 * k);
                }
                mma_rs<1, 1>(db, fe, de);
                wg_commit();
                bar_arrive<288>(next);
                dx ^= TB >> 4;
                de ^= 128;
                auto block = [&](int e) {
                    if (e > 0) fetch_group();
                    wg_wait();
                    keep(dv); keep(db); keep(fe);
#pragma unroll
                    for (int j = 0; j < NSTEP; j++) {
#pragma unroll
                        for (int r = 0; r < 2; r++) {
                            const uint32_t w = gate(e > 0 && j >= e ? hadd2(db[2 * j + r], hA[r]) : db[2 * j + r]);
                            hD[r] = hadd2(hD[r], w);
                            hN[r] = hfma2(w, dv[2 * j + r], hN[r]);
                        }
                        if (j + 1 == e) { flush_group(); init_group(); }
                    }
                };
                if (m == 0) block(0);
                else if (m & 1) {
                    if (m & 2) { if (m & 4) block(7); else block(3); } else { if (m & 4) block(5); else block(1); }
                } else {
                    if (m & 2) { if (m & 4) block(6); else block(2); } else { if (m & 4) block(4); else block(8); }
                }
            }
            PROF(10);
            for (uint32_t i = T, n = max_tiles(); i < n; i++) {
                bar_sync<288>(turn);
                bar_arrive<288>(next);
            }
            if (wg == 0) bar_sync<1, 288>();
            if (__any_sync(0xffffffffu, flags != 0)) redo_small(p, sm, flags, wg);
            asm volatile("{\n.reg .pred q;\nsetp.ge.u32 q, %1, 0x7c00;\nbar.red.or.pred q, %2, %3, q;\nselp.u32 %0, 1, 0, q;\n}"
                         : "=r"(plain) : "r"(hmag(nmax)), "n"((int)B_FINAL), "n"(NT) : "memory");
        }
        if (plain) slow_bin(p, sm, node0, nvalid);
        PROF(14);
    }
}

typedef CUresult (*EncodeFn)(CUtensorMap*, CUtensorMapDataType, cuuint32_t, void*, const cuuint64_t*, const cuuint64_t*,
                             const cuuint32_t*, const cuuint32_t*, CUtensorMapInterleave, CUtensorMapSwizzle,
                             CUtensorMapL2promotion, CUtensorMapFloatOOBfill);

}

extern "C" void kernel_launch(void* const* d_in, const int* in_sizes, int n_in, void* d_out, int out_size) {
    static int sms = 0;
    static EncodeFn encode = nullptr;
    static void *cell = nullptr, *ext = nullptr, *cnt = nullptr, *x16 = nullptr, *len = nullptr;
    if (!sms) {
        int dev = 0;
        cudaGetDevice(&dev);
        cudaDeviceGetAttribute(&sms, cudaDevAttrMultiProcessorCount, dev);
        cudaFuncSetAttribute(gatedgcn_kernel<1>, cudaFuncAttributeMaxDynamicSharedMemorySize, SM_TOTAL);
        cudaFuncSetAttribute(gatedgcn_kernel<2>, cudaFuncAttributeMaxDynamicSharedMemorySize, SM_TOTAL);
        cudaFuncSetAttribute(gatedgcn_kernel<3>, cudaFuncAttributeMaxDynamicSharedMemorySize, SM_TOTAL);
        cudaDriverEntryPointQueryResult qr;
        cudaGetDriverEntryPoint("cuTensorMapEncodeTiled", (void**)&encode, cudaEnableDefault, &qr);
        cudaGetSymbolAddress(&cell, g_cell);
        cudaGetSymbolAddress(&ext, g_ext);
        cudaGetSymbolAddress(&cnt, g_cnt);
        cudaGetSymbolAddress(&len, g_len);
        cudaGetSymbolAddress(&x16, g_x16);
        if (((uint64_t)x16 >> 32) != (((uint64_t)x16 + G * NSLOT * 128 - 1) >> 32)) x16 = (char*)x16 + G * NSLOT * 128;
    }
    Params p;
    p.x = (const __nv_bfloat16*)d_in[0];
    p.e = (const __nv_bfloat16*)d_in[1];
    p.src = (const int*)d_in[2];
    p.dst = (const int*)d_in[3];
    p.wa = (const __nv_bfloat16*)d_in[4];
    p.wb = (const __nv_bfloat16*)d_in[5];
    p.wc = (const __nv_bfloat16*)d_in[6];
    p.wu = (const __nv_bfloat16*)d_in[7];
    p.wv = (const __nv_bfloat16*)d_in[8];
    p.out = (__nv_bfloat16*)d_out;
    p.cell = (uint4*)cell;
    p.ext = (uint64_t*)ext;
    p.len = (uint32_t*)len;
    p.cnt = (uint32_t*)cnt;
    p.x16 = (const uint4*)x16;
    p.N = in_sizes[0] / 64;
    p.E = in_sizes[2];
    p.npc = (p.N + G - 1) / G;
    p.chunk = ((p.E + G - 1) / G + 7) & ~7;
    p.magic = (uint32_t)(0x100000000ull / (uint32_t)p.npc) + 1u;
    if (!encode || p.npc > NROW || p.N - (G - 1) * p.npc < 8 * NWG || p.chunk > CHUNK_MAX || (p.E & 7) ||
        p.E - (G - 1) * p.chunk <= (NWG - 1) * VWG * 4) return;

    CUtensorMap xmap, hmap;
    const cuuint64_t dims[2] = {64, (cuuint64_t)p.N};
    const cuuint64_t strides[1] = {128};
    const cuuint32_t box[2] = {64, XROWS}, estr[2] = {1, 1};
    encode(&xmap, CU_TENSOR_MAP_DATA_TYPE_BFLOAT16, 2, d_in[0], dims, strides, box, estr, CU_TENSOR_MAP_INTERLEAVE_NONE,
           CU_TENSOR_MAP_SWIZZLE_128B, CU_TENSOR_MAP_L2_PROMOTION_L2_256B, CU_TENSOR_MAP_FLOAT_OOB_FILL_NONE);
    encode(&hmap, CU_TENSOR_MAP_DATA_TYPE_FLOAT16, 2, x16, dims, strides, box, estr, CU_TENSOR_MAP_INTERLEAVE_NONE,
           CU_TENSOR_MAP_SWIZZLE_128B, CU_TENSOR_MAP_L2_PROMOTION_NONE, CU_TENSOR_MAP_FLOAT_OOB_FILL_NONE);
    if (sms >= G) {
        gatedgcn_kernel<3><<<G, NTA, SM_TOTAL>>>(p, xmap, hmap);
    } else {
        gatedgcn_kernel<1><<<G, NTA, SM_TOTAL>>>(p, xmap, hmap);
        gatedgcn_kernel<2><<<G, NTA, SM_TOTAL>>>(p, xmap, hmap);
    }
}
```

```cpp
#include <cuda_runtime.h>
#include <cuda_bf16.h>
#include <cuda_fp16.h>
#include <cuda.h>
#include <stdint.h>

namespace {

constexpr int G = 132;
constexpr int NWG = 4;
constexpr int NT = NWG * 128;
constexpr int NW = NT / 32;
constexpr int NTA = NT + 128;
constexpr int NSLOT = 384;
constexpr int NROW = 380;
constexpr int GPW = NSLOT / 8 / NWG;
constexpr int XROWS = NSLOT / NWG;
constexpr int VPT = 3;
constexpr int VWG = 128 * VPT;
constexpr int CHUNK_MAX = NT * VPT * 4;
constexpr int CV = 18;
constexpr int CX = 32;
constexpr int CAPC = 3 * CV + CX;
constexpr int LSTR = 160;
constexpr int BPR = NT / CV;
constexpr int RND = (G + BPR - 1) / BPR;
constexpr int RNC = (G * CV + NT - 1) / NT;
constexpr int TAILS = 192;
constexpr int NSTEP = 8;
constexpr int TB = NSTEP * 8 * 128;
constexpr int CAP = 6784;
constexpr int CAPX = CAP + NSTEP * 8;
constexpr int MAXT = 40;
static_assert(GPW % 2 == 0 && GPW <= 16 && G <= 192 && RNC == 5, "layout");

constexpr uint32_t SB = 1024;
constexpr int SM_RING = 0;
constexpr int SM_W = SM_RING + NSLOT * 128;
constexpr int SM_TBL = SM_W + 4 * 8192;
constexpr int SM_ENT = SM_TBL + NROW * 256;
constexpr int SM_EXT = SM_ENT + CHUNK_MAX * 6;
constexpr int SM_DEG = SM_EXT + 4096;
constexpr int SM_DH = SM_DEG + 512 * 4;
constexpr int SM_LG = SM_DH + 64 * 4;
constexpr int SM_END = SM_LG + 64 * 4;
constexpr int SM_MISC = SM_END + NWG * MAXT * 4;
constexpr int SM_HIST = SM_MISC + 64;
constexpr int SM_CUR = SM_HIST + 144 * 4;
constexpr int SM_GI = SM_CUR + 512 * 4;
constexpr int SM_TAIL = SM_GI + (NWG * GPW + 1) * 64;
constexpr int SM_BAR = SM_TAIL + TAILS * 4;
constexpr int SM_LBAR = SM_BAR + 96;
constexpr int SM_WC = SM_LBAR + 32;
constexpr int SM_TOTAL = SM_WC + 128;
constexpr int LND = 2 * NT * 16;
constexpr int SM_LND2 = SM_TBL + (NWG - 1) * XROWS * 256;
static_assert(SM_TOTAL <= 232448 && NSLOT * 128 * 4 <= SM_DEG, "smem");
static_assert(NWG * 2 * TB <= SM_W + 16384 && SM_TBL % 1024 == 0 && SM_EXT % 1024 == 0 && (SB + SM_EXT) % 4096 < 2048, "align");
static_assert((G + 1) * CAPC * 8 <= NROW * 256 && CAPC % 2 == 0, "outgoing cells");
static_assert(CAPX * 4 <= CHUNK_MAX * 6 && 2 * LND <= CHUNK_MAX * 6 && SM_LND2 + G * CV * 16 - 2 * LND <= SM_ENT, "aliases");
static_assert(SM_CUR % 16 == 0 && SM_GI % 16 == 0 && SM_WC % 16 == 0, "vector access");
enum { M_NOFIT, M_NTAIL, M_XBIG, M_XBAD, M_RANGE, M_SKIP, M_EPOCH, M_STEP0 = 8 };
enum { B_EDGE = 6, B_NODE, B_SENT, B_FINAL, B_CONV, B_COUNT, B_TAIL, B_READY, B_SORT };

__device__ __align__(128) uint4 g_cell[G * G * CV];
__device__ __align__(128) uint64_t g_ext[G * G * CX];
__device__ __align__(128) uint32_t g_len[G * LSTR];
__device__ __align__(128) uint4 g_x16[2 * G * NSLOT * 8];
__device__ __align__(128) uint32_t g_cnt[64];
#define PROFT(i, t)
#define PROF(i) PROFT(i, 0)

constexpr uint32_t DEN0 = 0x00220022u;
constexpr uint32_t DEN_SMALL = 0x03470347u;
constexpr uint32_t E_PAD = 0xffff0000u;
constexpr uint32_t H_MAX = 0x4ff0u;
constexpr uint32_t A_MAX = 0x5000u;
constexpr uint32_t SQ_MAX = 0x6380u;
constexpr uint32_t SQ_MIN = 0x2240u;

__device__ __forceinline__ float tanh_(float x) { float y; asm("tanh.approx.f32 %0, %1;" : "=f"(y) : "f"(x)); return y; }
__device__ __forceinline__ float rcp(float x) { float y; asm("rcp.approx.ftz.f32 %0, %1;" : "=f"(y) : "f"(x)); return y; }
__device__ __forceinline__ uint32_t pack_bf16(float lo, float hi) { uint32_t r; asm("cvt.rn.bf16x2.f32 %0, %1, %2;" : "=r"(r) : "f"(hi), "f"(lo)); return r; }
__device__ __forceinline__ uint32_t pack_h(float lo, float hi) { uint32_t r; asm("cvt.rn.f16x2.f32 %0, %1, %2;" : "=r"(r) : "f"(hi), "f"(lo)); return r; }
__device__ __forceinline__ float h_lo(uint32_t v) { return __low2float(*reinterpret_cast<__half2*>(&v)); }
__device__ __forceinline__ float h_hi(uint32_t v) { return __high2float(*reinterpret_cast<__half2*>(&v)); }
__device__ __forceinline__ uint32_t hadd2(uint32_t a, uint32_t b) { uint32_t r; asm("add.rn.f16x2 %0, %1, %2;" : "=r"(r) : "r"(a), "r"(b)); return r; }
__device__ __forceinline__ uint32_t hsub2(uint32_t a, uint32_t b) { uint32_t r; asm("sub.rn.f16x2 %0, %1, %2;" : "=r"(r) : "r"(a), "r"(b)); return r; }
__device__ __forceinline__ uint32_t hfma2(uint32_t a, uint32_t b, uint32_t c) { uint32_t r; asm("fma.rn.f16x2 %0, %1, %2, %3;" : "=r"(r) : "r"(a), "r"(b), "r"(c)); return r; }
__device__ __forceinline__ uint32_t hamax2(uint32_t a, uint32_t b) { uint32_t r; asm("max.NaN.xorsign.abs.f16x2 %0, %1, %2;" : "=r"(r) : "r"(a), "r"(b)); return r; }
__device__ __forceinline__ uint32_t hmag(uint32_t m) { return max(m & 0x7fffu, (m >> 16) & 0x7fffu); }
__device__ __forceinline__ float bf_lo(uint32_t v) { return __uint_as_float(v << 16); }
__device__ __forceinline__ float bf_hi(uint32_t v) { return __uint_as_float(v & 0xffff0000u); }
__device__ __forceinline__ uint32_t bf2h(uint32_t v) { return pack_h(bf_lo(v), bf_hi(v)); }
__device__ __forceinline__ uint32_t finish2(float z0, float z1, uint32_t x) {
    uint32_t z, o;
    asm("cvt.rn.relu.bf16x2.f32 %0, %1, %2;" : "=r"(z) : "f"(z1), "f"(z0));
    asm("fma.rn.bf16x2 %0, %1, %2, %3;" : "=r"(o) : "r"(z), "r"(0x3b803b80u), "r"(x));
    return o;
}
__device__ __forceinline__ uint32_t opaque32(uint32_t v) { asm volatile("" : "+r"(v)); return v; }
__device__ __forceinline__ uint2 lds64(uint32_t a) { uint2 v; asm volatile("ld.shared.v2.u32 {%0,%1}, [%2];" : "=r"(v.x), "=r"(v.y) : "r"(a)); return v; }
__device__ __forceinline__ uint4 lds128(uint32_t a) {
    uint4 v;
    asm("ld.shared.v4.u32 {%0,%1,%2,%3}, [%4];" : "=r"(v.x), "=r"(v.y), "=r"(v.z), "=r"(v.w) : "r"(a));
    return v;
}
__device__ __forceinline__ uint32_t ldg32(const void* p) { uint32_t v; asm("ld.global.nc.u32 %0, [%1];" : "=r"(v) : "l"(p)); return v; }

__device__ __forceinline__ void spin_limit(uint32_t it) {
    asm volatile("{\n.reg .pred q;\n.reg .b64 z;\nmov.b64 z, 0;\nsetp.gt.u32 q, %0, 0x400000;\n@q st.global.u32 [z], %0;\n}" ::"r"(it));
}
__device__ __forceinline__ void wg_fence() { asm volatile("wgmma.fence.sync.aligned;" ::: "memory"); }
__device__ __forceinline__ void wg_commit() { asm volatile("wgmma.commit_group.sync.aligned;" ::: "memory"); }
__device__ __forceinline__ void wg_wait() { asm volatile("wgmma.wait_group.sync.aligned 0;" ::: "memory"); }
__device__ __forceinline__ void proxy_fence() { asm volatile("fence.proxy.async.shared::cta;" ::: "memory"); }
__device__ __forceinline__ void cp_commit() { asm volatile("cp.async.commit_group;" ::: "memory"); }
__device__ __forceinline__ void cp_wait() { asm volatile("cp.async.wait_group 0;" ::: "memory"); }
__device__ __forceinline__ void cp16(uint32_t dst, const void* src) { asm volatile("cp.async.cg.shared.global [%0], [%1], 16;" ::"r"(dst), "l"(src) : "memory"); }
template <int ID, int N> __device__ __forceinline__ void bar_sync() { asm volatile("bar.sync %0, %1;" ::"n"(ID), "n"(N) : "memory"); }
template <int ID, int N> __device__ __forceinline__ void bar_arrive() { asm volatile("bar.arrive %0, %1;" ::"n"(ID), "n"(N) : "memory"); }
template <int N> __device__ __forceinline__ void bar_sync(uint32_t id) { asm volatile("bar.sync %0, %1;" ::"r"(id), "n"(N) : "memory"); }
template <int N> __device__ __forceinline__ void bar_arrive(uint32_t id) { asm volatile("bar.arrive %0, %1;" ::"r"(id), "n"(N) : "memory"); }
__device__ __forceinline__ uint32_t ld_relaxed(const uint32_t* p) {
    uint32_t v;
    asm volatile("ld.relaxed.gpu.global.u32 %0, [%1];" : "=r"(v) : "l"(p) : "memory");
    return v;
}
__device__ __forceinline__ void st_relaxed(uint32_t* p, uint32_t v) { asm volatile("st.relaxed.gpu.global.u32 [%0], %1;" ::"l"(p), "r"(v) : "memory"); }
__device__ __forceinline__ uint2 ld_relaxed8(const void* p) {
    uint2 v;
    asm volatile("{\n.reg .b64 t;\nld.relaxed.gpu.global.b64 t, [%2];\nmov.b64 {%0, %1}, t;\n}" : "=r"(v.x), "=r"(v.y) : "l"(p) : "memory");
    return v;
}
__device__ __forceinline__ void st_relaxed8(void* p, uint32_t lo, uint32_t hi) {
    asm volatile("{\n.reg .b64 t;\nmov.b64 t, {%1, %2};\nst.relaxed.gpu.global.b64 [%0], t;\n}" ::"l"(p), "r"(lo), "r"(hi) : "memory");
}
__device__ __forceinline__ void bulk_load(uint32_t dst, const void* src, uint32_t bytes, uint32_t bar) {
    asm volatile("cp.async.bulk.shared::cluster.global.mbarrier::complete_tx::bytes [%0], [%1], %2, [%3];"
                 ::"r"(dst), "l"(src), "r"(bytes), "r"(bar) : "memory");
}
__device__ __forceinline__ void mbar_init(uint32_t bar) { asm volatile("mbarrier.init.shared::cta.b64 [%0], 1;" ::"r"(bar) : "memory"); }
__device__ __forceinline__ void expect_tx(uint32_t bar, uint32_t bytes) {
    asm volatile("mbarrier.arrive.expect_tx.shared::cta.b64 _, [%0], %1;" ::"r"(bar), "r"(bytes) : "memory");
}
__device__ __forceinline__ bool mbar_try(uint32_t bar) {
    uint32_t ok;
    asm volatile("{\n.reg .pred q;\nmbarrier.try_wait.parity.shared::cta.b64 q, [%1], 0;\nselp.u32 %0, 1, 0, q;\n}"
                 : "=r"(ok) : "r"(bar) : "memory");
    return ok;
}
__device__ __forceinline__ void mbar_wait(uint32_t bar) {
    for (uint32_t it = 0; !mbar_try(bar); it++) spin_limit(it);
}
__device__ __forceinline__ void ld_relaxed16_if(uint4& v, const uint4* p, bool on) {
    asm volatile("{\n.reg .pred q;\n.reg .b128 t;\n.reg .b64 a, b;\nsetp.ne.u32 q, %5, 0;\n"
                 "mov.b64 a, {%0, %1};\nmov.b64 b, {%2, %3};\nmov.b128 t, {a, b};\n@q ld.relaxed.gpu.global.b128 t, [%4];\n"
                 "mov.b128 {a, b}, t;\nmov.b64 {%0, %1}, a;\nmov.b64 {%2, %3}, b;\n}"
                 : "+r"(v.x), "+r"(v.y), "+r"(v.z), "+r"(v.w) : "l"(p), "r"((uint32_t)on) : "memory");
}
__device__ __forceinline__ void st_relaxed16(uint4* p, uint4 v) {
    asm volatile("{\n.reg .b128 t;\n.reg .b64 a, b;\nmov.b64 a, {%1, %2};\nmov.b64 b, {%3, %4};\nmov.b128 t, {a, b};\n"
                 "st.relaxed.gpu.global.b128 [%0], t;\n}"
                 ::"l"(p), "r"(v.x), "r"(v.y), "r"(v.z), "r"(v.w) : "memory");
}

#define R4(d, o) "+r"(d[o]), "+r"(d[o + 1]), "+r"(d[o + 2]), "+r"(d[o + 3])
#define L16 "%0,%1,%2,%3,%4,%5,%6,%7,%8,%9,%10,%11,%12,%13,%14,%15"
#define L24 L16 ",%16,%17,%18,%19,%20,%21,%22,%23"
constexpr uint32_t HI_SW = 0x40000000u | 64u;
template <int A>
__device__ __forceinline__ void mma_ss(uint32_t (&d)[24], uint32_t alo, uint32_t blo) {
    asm volatile("{\n.reg .b64 a, b;\nmov.b64 a, {%24, %26};\nmov.b64 b, {%25, %26};\n"
                 "wgmma.mma_async.sync.aligned.m64n96k16.f16.f16.f16 {" L24 "}, a, b, %27, 1, 1, 1, 0;\n}\n"
                 : R4(d, 0), R4(d, 4), R4(d, 8), R4(d, 12), R4(d, 16), R4(d, 20)
                 : "r"(alo), "r"(blo), "r"(HI_SW), "n"(A));
}
template <int A, int T>
__device__ __forceinline__ void mma_rs(uint32_t (&d)[16], const uint32_t* a, uint32_t blo) {
    asm volatile("{\n.reg .b64 b;\nmov.b64 b, {%20, %21};\n"
                 "wgmma.mma_async.sync.aligned.m64n64k16.f16.f16.f16 {" L16 "}, {%16,%17,%18,%19}, b, %22, 1, 1, %23;\n}\n"
                 : R4(d, 0), R4(d, 4), R4(d, 8), R4(d, 12)
                 : "r"(a[0]), "r"(a[1]), "r"(a[2]), "r"(a[3]), "r"(blo), "r"(HI_SW), "n"(A), "n"(T));
}
template <int R> __device__ __forceinline__ void keep(uint32_t (&d)[R]) {
#pragma unroll
    for (int i = 0; i < R; i++) asm volatile("" : "+r"(d[i])::"memory");
}
__device__ __forceinline__ void ldsm_t(uint32_t* f, uint32_t addr) {
    asm volatile("ldmatrix.sync.aligned.m8n8.x4.trans.shared.b16 {%0,%1,%2,%3}, [%4];"
                 : "=r"(f[0]), "=r"(f[1]), "=r"(f[2]), "=r"(f[3]) : "r"(addr) : "memory");
}
__device__ __forceinline__ uint32_t stage_w(unsigned char* mat, int k, int c, uint4 a, uint4 b, float s) {
    unsigned char* row = mat + k * 128;
    const uint4 e = make_uint4(pack_h(s * bf_lo(a.x), s * bf_lo(a.y)), pack_h(s * bf_lo(a.z), s * bf_lo(a.w)),
                               pack_h(s * bf_lo(b.x), s * bf_lo(b.y)), pack_h(s * bf_lo(b.z), s * bf_lo(b.w)));
    const uint4 o = make_uint4(pack_h(s * bf_hi(a.x), s * bf_hi(a.y)), pack_h(s * bf_hi(a.z), s * bf_hi(a.w)),
                               pack_h(s * bf_hi(b.x), s * bf_hi(b.y)), pack_h(s * bf_hi(b.z), s * bf_hi(b.w)));
    *reinterpret_cast<uint4*>(row + ((c ^ (k & 7)) << 4)) = e;
    *reinterpret_cast<uint4*>(row + (((c + 1) ^ (k & 7)) << 4)) = o;
    return hamax2(hamax2(hamax2(e.x, e.y), hamax2(e.z, e.w)), hamax2(hamax2(o.x, o.y), hamax2(o.z, o.w)));
}

struct Params {
    const int* dst;
    const int* src;
    const __nv_bfloat16* e;
    int N, E, npc, chunk;
    const __nv_bfloat16* x;
    __nv_bfloat16* out;
    uint32_t* cnt;
    const __nv_bfloat16 *wa, *wb, *wc, *wu, *wv;
    uint4* cell;
    uint64_t* ext;
    uint32_t* len;
    const uint4* x16;
    uint32_t magic;
};

__device__ __noinline__ void slow_bin(const Params& p, unsigned char* sm, int node0, int nvalid) {
    float* acc = reinterpret_cast<float*>(sm);
    const int tid = threadIdx.x, lane = tid & 31, warp = tid >> 5;
    bar_sync<B_EDGE, NT>();
    for (int i = tid; i < NSLOT * 128; i += NT) acc[i] = 0.f;
    bar_sync<B_EDGE, NT>();
    const uint32_t* x2 = reinterpret_cast<const uint32_t*>(p.x);
    const uint32_t* wb = reinterpret_cast<const uint32_t*>(p.wb) + lane;
    const uint32_t* wv = reinterpret_cast<const uint32_t*>(p.wv) + lane;
    const uint32_t* wa = reinterpret_cast<const uint32_t*>(p.wa) + lane;
    const uint32_t* wu = reinterpret_cast<const uint32_t*>(p.wu) + lane;
    const uint32_t wc = reinterpret_cast<const uint32_t*>(p.wc)[lane];
    for (int i0 = warp * 32; i0 < p.E; i0 += NT) {
        const int dl = i0 + lane < p.E ? p.dst[i0 + lane] - node0 : -1;
        uint32_t m = __ballot_sync(0xffffffffu, (uint32_t)dl < (uint32_t)nvalid);
        while (m) {
            const int l = __ffs(m) - 1;
            m &= m - 1;
            const int d = __shfl_sync(0xffffffffu, dl, l);
            const uint32_t xs = x2[p.src[i0 + l] * 32 + lane], xd = x2[(node0 + d) * 32 + lane];
            float g0 = 0.f, g1 = 0.f, v0 = 0.f, v1 = 0.f;
#pragma unroll 4
            for (int k = 0; k < 32; k++) {
                const uint32_t a = __shfl_sync(0xffffffffu, xs, k), b = __shfl_sync(0xffffffffu, xd, k);
#pragma unroll
                for (int h = 0; h < 2; h++) {
                    const float fs = h ? bf_hi(a) : bf_lo(a), fd = h ? bf_hi(b) : bf_lo(b);
                    const uint32_t ua = wa[(2 * k + h) * 32], ub = wb[(2 * k + h) * 32], uv = wv[(2 * k + h) * 32];
                    g0 += fd * bf_lo(ua) + fs * bf_lo(ub);
                    g1 += fd * bf_hi(ua) + fs * bf_hi(ub);
                    v0 += fs * bf_lo(uv);
                    v1 += fs * bf_hi(uv);
                }
            }
            const float ev = __bfloat162float(p.e[i0 + l]);
            const float e0 = rcp(1.f + __expf(-(g0 + ev * bf_lo(wc))));
            const float e1 = rcp(1.f + __expf(-(g1 + ev * bf_hi(wc))));
            float* a = acc + d * 128 + 2 * lane;
            atomicAdd(a, e0);
            atomicAdd(a + 1, e1);
            atomicAdd(a + 64, e0 * v0);
            atomicAdd(a + 65, e1 * v1);
        }
    }
    bar_sync<B_EDGE, NT>();
    for (int n = warp; n < nvalid; n += NW) {
        const uint32_t xd = x2[(node0 + n) * 32 + lane];
        float u0 = 0.f, u1 = 0.f;
#pragma unroll 4
        for (int k = 0; k < 32; k++) {
            const uint32_t b = __shfl_sync(0xffffffffu, xd, k);
            const uint32_t w0 = wu[(2 * k) * 32], w1 = wu[(2 * k + 1) * 32];
            u0 += bf_lo(b) * bf_lo(w0) + bf_hi(b) * bf_lo(w1);
            u1 += bf_lo(b) * bf_hi(w0) + bf_hi(b) * bf_hi(w1);
        }
        const float* a = acc + n * 128 + 2 * lane;
        const float z0 = u0 + a[64] * rcp(a[0] + 1e-6f), z1 = u1 + a[65] * rcp(a[1] + 1e-6f);
        const float r0 = z0 > 0.f ? z0 : 0.f * z0, r1 = z1 > 0.f ? z1 : 0.f * z1;
        reinterpret_cast<uint32_t*>(p.out)[(node0 + n) * 32 + lane] = pack_bf16(bf_lo(xd) + r0, bf_hi(xd) + r1);
    }
}

__device__ __noinline__ void redo_small(const void* px, const void* pwb, const void* pwv, const void* pwc, void* pout,
                                        uint32_t flags, int wg, int node0) {
    extern __shared__ __align__(1024) unsigned char sm[];
    const int lane = threadIdx.x & 31, g = lane >> 2, t = lane & 3;
    uint32_t i0 = 0;
    float den = 0.f, num = 0.f;
#pragma unroll 1
    for (uint32_t m; (m = __ballot_sync(0xffffffffu, flags != 0)) != 0;) {
        const int l = __ffs(m) - 1;
        const uint32_t k = __ffs(__shfl_sync(0xffffffffu, flags, l)) - 1;
        const uint32_t pr = ((threadIdx.x >> 5) & 3) * 8 + (l >> 2);
        const uint32_t ta = reinterpret_cast<const uint2*>(sm + SM_GI)[(wg * GPW + (k & 15) - (16 - GPW)) * 8 + 2 * (l & 3) + (k >> 4)].x;
        const uint32_t n = (ta - SB - SM_TBL) >> 8;
        const uint32_t deg = reinterpret_cast<const uint32_t*>(sm + SM_DEG)[n];
        const uint32_t base = (reinterpret_cast<const uint32_t*>(sm + SM_CUR)[n] >> 2) - 8 * deg;
        const uint2 tb = lds64(ta ^ (pr * 8));
        uint4 xr[4][2];
        uint32_t en[4], wr[16];
#pragma unroll
        for (int u = 0; u < 4; u++) {
            en[u] = reinterpret_cast<const uint32_t*>(sm + SM_ENT)[base + 8 * min(i0 + 8 * u + g, max(deg, 1u) - 1)];
            xr[u][0] = __ldg(reinterpret_cast<const uint4*>(px) + (en[u] & 0xffff) * 8 + 2 * t);
            xr[u][1] = __ldg(reinterpret_cast<const uint4*>(px) + (en[u] & 0xffff) * 8 + 2 * t + 1);
        }
        const uint16_t* w = reinterpret_cast<const uint16_t*>((g & 1) ? pwv : pwb) + 16 * t * 64 + 2 * pr + ((g >> 1) & 1);
#pragma unroll
        for (int i = 0; i < 16; i++) wr[i] = __ldg(w + i * 64);
        uint32_t x;
        asm volatile("ld.volatile.global.u32 %0, [%1];" : "=r"(x) : "l"(reinterpret_cast<const uint32_t*>(px) + (node0 + n) * 32 + pr));
        const float wc = bf_lo(__ldg(reinterpret_cast<const uint16_t*>(pwc) + 2 * pr + (t & 1)));
        const float a = 2.f * ((t & 1) ? h_hi(tb.x) : h_lo(tb.x));
#pragma unroll
        for (int u = 0; u < 4; u += 2) {
            float c[4] = {0.f, 0.f, 0.f, 0.f};
#pragma unroll
            for (int q = 0; q < 4; q++) {
                const uint4 r0 = xr[u][q >> 1], r1 = xr[u + 1][q >> 1];
                asm("mma.sync.aligned.m16n8k16.row.col.f32.bf16.bf16.f32 {%0,%1,%2,%3}, {%4,%5,%6,%7}, {%8,%9}, {%0,%1,%2,%3};"
                    : "+f"(c[0]), "+f"(c[1]), "+f"(c[2]), "+f"(c[3])
                    : "r"((q & 1) ? r0.z : r0.x), "r"((q & 1) ? r1.z : r1.x), "r"((q & 1) ? r0.w : r0.y), "r"((q & 1) ? r1.w : r1.y),
                      "r"(wr[4 * q] | wr[4 * q + 1] << 16), "r"(wr[4 * q + 2] | wr[4 * q + 3] << 16));
            }
#pragma unroll
            for (int h = 0; h < 2; h++) {
                float eta = rcp(1.f + __expf(-(a + c[2 * h] + h_hi(en[u + h]) * wc)));
                eta = i0 + 8 * (u + h) + g < deg ? eta : 0.f;
                den += eta;
                num += eta * c[2 * h + 1];
            }
        }
        i0 += 32;
        if (i0 >= deg) {
#pragma unroll
            for (int o = 4; o < 32; o <<= 1) { den += __shfl_xor_sync(0xffffffffu, den, o); num += __shfl_xor_sync(0xffffffffu, num, o); }
            const float agg = 256.f * num * rcp(den + 1e-6f);
            const uint32_t o = finish2(__shfl_sync(0xffffffffu, agg, 0) + h_lo(tb.y), __shfl_sync(0xffffffffu, agg, 1) + h_hi(tb.y), x);
            if (lane == l) {
                if (!(ta & 8)) reinterpret_cast<uint32_t*>(pout)[(node0 + n) * 32 + pr] = o;
                flags &= flags - 1;
            }
            i0 = 0; den = 0.f; num = 0.f;
        }
    }
}

template <int MODE>
__global__ void __launch_bounds__(NTA, 1) gatedgcn_kernel(const __grid_constant__ Params p, const __grid_constant__ CUtensorMap xmap,
                                                          const __grid_constant__ CUtensorMap hmap) {
    extern __shared__ __align__(1024) unsigned char sm[];
    constexpr uint32_t sb = SB;
    spin_limit((uint32_t)__cvta_generic_to_shared(sm) != SB ? ~0u : 0u);
    const int tid = threadIdx.x, lane = tid & 31;
    const int warp = __shfl_sync(0xffffffffu, tid >> 5, 0);
    const int wg = warp >> 2, w4 = warp & 3, g8 = lane >> 2, t4 = lane & 3, tw = tid & 127;
    const int cta = blockIdx.x;
    const int node0 = cta * p.npc;
    const int nvalid = min(p.npc, p.N - node0);
    const int ch = 16 * w4 + 2 * g8;
    const uint64_t xa = reinterpret_cast<uint64_t>(p.x) + (uint64_t)node0 * 128, oa = reinterpret_cast<uint64_t>(p.out) + (uint64_t)node0 * 128;
    const uint32_t xrow0 = (uint32_t)xa;

    const uint32_t share = cta == 0 ? 1024 - G + 1 : 1;

    uint32_t* s_hist = reinterpret_cast<uint32_t*>(sm + SM_HIST);
    uint32_t* s_deg = reinterpret_cast<uint32_t*>(sm + SM_DEG);
    uint32_t* s_cur = reinterpret_cast<uint32_t*>(sm + SM_CUR);
    uint2* s_gi = reinterpret_cast<uint2*>(sm + SM_GI);
    uint32_t* s_dh = reinterpret_cast<uint32_t*>(sm + SM_DH);
    uint32_t* s_lg = reinterpret_cast<uint32_t*>(sm + SM_LG);
    uint32_t* s_end = reinterpret_cast<uint32_t*>(sm + SM_END);
    uint32_t* s_tail = reinterpret_cast<uint32_t*>(sm + SM_TAIL);
    uint32_t* s_misc = reinterpret_cast<uint32_t*>(sm + SM_MISC);
    uint32_t* s_ent = reinterpret_cast<uint32_t*>(sm + SM_ENT);
    auto max_tiles = [&]() {
        uint32_t tm = 0;
#pragma unroll
        for (int k = 0; k < NWG; k++) tm = max(tm, (s_misc[M_STEP0 + 1 + k] - s_misc[M_STEP0 + k] + NSTEP - 1) / NSTEP);
        return tm;
    };

    PROF(0);
    if (wg == NWG) {
        if (tw == 0) {
#pragma unroll
            for (int i = 0; i < 4; i++) mbar_init(sb + SM_LBAR + 8 * i);
            proxy_fence();
            if (MODE & 2) {
                expect_tx(sb + SM_LBAR + 24, 4 * 8192 + 128);
                bulk_load(sb + SM_W, p.wa, 8192, sb + SM_LBAR + 24);
                bulk_load(sb + SM_W + 8192, p.wu, 8192, sb + SM_LBAR + 24);
                bulk_load(sb + SM_W + 16384, p.wb, 8192, sb + SM_LBAR + 24);
                bulk_load(sb + SM_W + 24576, p.wv, 8192, sb + SM_LBAR + 24);
                bulk_load(sb + SM_WC, p.wc, 128, sb + SM_LBAR + 24);
            }
        }
        asm volatile("setmaxnreg.dec.sync.aligned.u32 32;");
        uint32_t mw = 0;
        if (MODE & 2) {
            {
                const int k = (tw >> 3) & 7;
                const uint32_t one = tw >= 64 ? 0x3c00u << (16 * (k & 1)) : 0u;
                const uint4 v = make_uint4(k >> 1 == 0 ? one : 0, k >> 1 == 1 ? one : 0, k >> 1 == 2 ? one : 0, k >> 1 == 3 ? one : 0);
                reinterpret_cast<uint4*>(sm + SM_EXT)[tw] = v;
                reinterpret_cast<uint4*>(sm + SM_EXT)[tw + 128] = v;
            }
            bar_sync<1 + NWG, 128>();
            mbar_wait(sb + SM_LBAR + 24);
            if (w4 == 0) {
                mw = reinterpret_cast<uint32_t*>(sm + SM_WC)[lane];
                mw = pack_h(0.5f * bf_lo(mw), 0.5f * bf_hi(mw));
                reinterpret_cast<uint32_t*>(sm + SM_WC)[lane] = mw;
                mw = hmag(mw);
            }
#pragma unroll 1
            for (int j = 0; j < 8; j++) {
                const uint4* w = reinterpret_cast<const uint4*>(sm + SM_W + j * 4096) + tw * 2;
                const uint4 a = w[0], b = w[1];
                __syncwarp();
                const uint32_t m = hmag(stage_w(sm + SM_W + j * 4096, tw >> 2, (tw & 3) * 2, a, b, (j & 2) ? 256.f : 0.5f));
                mw = max((int)mw, (int)m - ((j & 2) ? 8 << 10 : 0));
            }
        }
        proxy_fence();
        bar_sync<B_SENT, NTA>();
        const uint32_t epoch = s_misc[M_EPOCH];
        if (mw > H_MAX) s_misc[M_RANGE] = 1;
        if (w4 == 0) {
            if (MODE == 3) {
                if (lane == 0) for (uint32_t it = 0; ld_relaxed(p.cnt) != epoch << 10; it++) spin_limit(it);
                __syncwarp();
                bar_arrive<B_READY, 128>();
            }
            if ((MODE & 2) && lane == 0) {
                const uint4* in = p.cell + cta * G * CV;
                proxy_fence();
                expect_tx(sb + SM_LBAR, LND);
                bulk_load(sb + SM_ENT, in, LND, sb + SM_LBAR);
                expect_tx(sb + SM_LBAR + 8, LND);
                bulk_load(sb + SM_ENT + LND, in + LND / 16, LND, sb + SM_LBAR + 8);
                expect_tx(sb + SM_LBAR + 16, G * CV * 16 - 2 * LND);
                bulk_load(sb + SM_LND2, in + LND / 8, G * CV * 16 - 2 * LND, sb + SM_LBAR + 16);
            }
            PROFT(11, NT);
            if (MODE & 1) bar_sync<B_CONV, NT + 32>();
            if (lane == 0) {
                if (MODE & 1) {
#pragma unroll 1
                    for (int b = 0; b < NWG; b++)
                        asm volatile("cp.async.bulk.tensor.2d.global.shared::cta.bulk_group [%0, {%2, %3}], [%1];"
                                     ::"l"(&hmap), "r"(sb + SM_RING + b * XROWS * 128), "r"(0), "r"(node0 + b * XROWS) : "memory");
                    asm volatile("cp.async.bulk.commit_group;" ::: "memory");
                    PROFT(12, NT);
                    if (s_misc[M_XBAD]) st_relaxed(p.cnt + 33, epoch);
                    asm volatile("cp.async.bulk.wait_group 0;" ::: "memory");
                    PROFT(13, NT);
                    asm volatile("red.release.gpu.global.add.u32 [%0], %1;" ::"l"(p.cnt + 32), "r"(share) : "memory");
                }
                if (MODE & 2) {
                    uint2 c = ld_relaxed8(p.cnt + 32);
                    for (uint32_t it = 0; c.x != epoch << 10; it++) { c = ld_relaxed8(p.cnt + 32); spin_limit(it); }
                    asm volatile("fence.acquire.gpu;" ::: "memory");
                    if (c.y == epoch) s_misc[M_RANGE] = 1;
                }
                PROFT(15, NT);
            }
            __syncwarp();
        } else if (MODE & 2) {
            const uint32_t tag23 = epoch << 9;
            const int t = tw - 32;
            uint32_t ln[2] = {~tag23, t < G - 96 ? ~tag23 : tag23};
            for (uint32_t it = 0; ((ln[0] ^ tag23) | (ln[1] ^ tag23)) > 0x1ff; it++) {
#pragma unroll
                for (int r = 0; r < 2; r++)
                    if ((ln[r] ^ tag23) > 0x1ff) ln[r] = ld_relaxed(p.len + cta * LSTR + t + 96 * r);
                spin_limit(it);
            }
#pragma unroll
            for (int r = 0; r < 2; r++) {
                const int n = (int)(ln[r] & 0x1ff) - 3 * CV;
                if (n > 0) {
                    const uint32_t o = atomicAdd(&s_misc[M_NTAIL], n);
                    if (n > CX || o + n > TAILS) s_misc[M_NOFIT] = 1;
                    else for (int k = 0; k < n; k++) s_tail[o + k] = (t + 96 * r) * CX + k;
                }
            }
            bar_sync<B_TAIL, 96>();
            const uint32_t nt = s_misc[M_NOFIT] ? 0 : s_misc[M_NTAIL];
            const uint64_t* ep[2];
            uint2 v[2];
#pragma unroll
            for (int r = 0; r < 2; r++) {
                ep[r] = p.ext + cta * G * CX + (t + 96 * r < nt ? s_tail[t + 96 * r] : 0);
                v[r] = make_uint2(0, t + 96 * r < nt ? ~tag23 : tag23 | 511);
            }
            PROFT(1, NT + 32);
            if (MODE == 3) bar_sync<B_READY, 128>();
            for (uint32_t it = 0; ((v[0].y ^ tag23) | (v[1].y ^ tag23)) > 0x1ff; it++) {
#pragma unroll
                for (int r = 0; r < 2; r++)
                    if ((v[r].y ^ tag23) > 0x1ff) v[r] = ld_relaxed8(ep[r]);
                spin_limit(it);
            }
            atomicAdd(&s_deg[v[0].y & 0x1ff], 1u);
            atomicAdd(&s_deg[v[1].y & 0x1ff], 1u);
            PROFT(2, NT + 32);
            bar_sync<B_COUNT, NT + 96>();
            const uint32_t pv = node0 | E_PAD;
            for (int k = t; k < CAPX / 4; k += 96) reinterpret_cast<uint4*>(s_ent)[k] = make_uint4(pv, pv, pv, pv);
            bar_sync<B_SORT, NT + 96>();
            if (s_misc[M_SKIP] == 0) {
#pragma unroll
                for (int r = 0; r < 2; r++)
                    if (t + 96 * r < nt) s_ent[atomicAdd(&s_cur[v[r].y & 0x1ff], 32u) >> 2] = v[r].x;
            }
        }
        if (!(MODE & 2)) return;
        __syncthreads();
        if (s_misc[M_SKIP] | s_misc[M_RANGE] | (s_misc[M_XBIG] ^ 1)) return;
        const uint32_t step0 = s_misc[M_STEP0 + w4];
        const int T = (s_misc[M_STEP0 + 1 + w4] - step0 + NSTEP - 1) / NSTEP;
        const int q = lane >> 3, c8 = lane & 7;
        uint32_t sidx = sb + SM_ENT + step0 * 32 + q * 8;
        uint32_t sd0 = sb + SM_RING + w4 * (2 * TB) + q * 256 + ((c8 ^ (2 * q)) << 4);
        uint32_t se = sb + SM_EXT + w4 * 256 + ((c8 ^ (2 * w4)) << 4) + q * 4;
        const uint32_t xlo = (uint32_t)reinterpret_cast<uint64_t>(p.x16) + c8 * 16;
        const uint32_t xhi = (uint32_t)(reinterpret_cast<uint64_t>(p.x16) >> 32);
#pragma unroll 1
        for (int i = 0; i < T; i++) {
            uint2 nx[NSTEP];
            const uint2 ee = lds64(sidx + 32 * c8);
#pragma unroll
            for (int j = 0; j < NSTEP; j++) nx[j] = lds64(sidx + 32 * j);
            const uint32_t e2 = __byte_perm(ee.x, ee.y, 0x7632);
            uint32_t pm;
            asm("set.nan.u32.f16x2 %0, %1, %1;" : "=r"(pm) : "r"(e2));
            if (i > 0) {
                cp_wait();
                proxy_fence();
                bar_sync<288>(1 + w4);
            }
            asm volatile("st.shared.u32 [%0], %1;" ::"r"(se), "r"(e2 & ~pm) : "memory");
            asm volatile("st.shared.u32 [%0+128], %1;" ::"r"(se ^ 16), "r"(pm & 0x40004000u) : "memory");
#pragma unroll
            for (int u = 0; u < 2 * NSTEP; u++) {
                uint64_t ga;
                asm("{\n.reg .b32 lo;\ndp2a.lo.u32.u32 lo, %1, 0x80, %2;\nmov.b64 %0, {lo, %3};\n}"
                    : "=l"(ga) : "r"((u & 1) ? nx[u >> 1].y : nx[u >> 1].x), "r"(xlo), "r"(xhi));
                cp16((sd0 ^ ((u & 1) * 16)) + (u & 1) * 128 + (u >> 1) * 1024, reinterpret_cast<const void*>(ga));
            }
            cp_commit();
            sidx += NSTEP * 32;
            sd0 ^= TB;
            se ^= 2048;
        }
        cp_wait();
        proxy_fence();
        for (uint32_t i = T - 1, n = max_tiles() + (w4 == 0); i < n; i++) bar_sync<288>(1 + w4);
    } else {
        const uint32_t bar = sb + SM_BAR + wg * 24;
        const int e0 = cta * p.chunk + wg * VWG * 4;
        const int nvec = min(min(p.chunk - wg * VWG * 4, p.E - e0) >> 2, VWG);
        auto load_x = [&]() {
            if (tw == 0) {
                expect_tx(bar + 16, XROWS * 128);
                asm volatile("cp.async.bulk.tensor.2d.shared::cluster.global.mbarrier::complete_tx::bytes [%0], [%1, {%3, %4}], [%2];"
                             ::"r"(sb + SM_RING + wg * XROWS * 128), "l"(&xmap), "r"(bar + 16), "r"(0), "r"(node0 + wg * XROWS) : "memory");
            }
        };
        if (tw == 0) {
#pragma unroll
            for (int i = 0; i < 3; i++) mbar_init(bar + i * 8);
            proxy_fence();
            if (MODE & 1) {
                expect_tx(bar, nvec * 16);
                bulk_load(sb + SM_RING + wg * XROWS * 128, p.dst + e0, nvec * 16, bar);
            }
        }
        if (MODE == 2) load_x();
        const uint32_t cnt0 = ld_relaxed(p.cnt + opaque32(0));

        if (tid < (SM_CUR - SM_DEG) / 16) reinterpret_cast<uint4*>(sm + SM_DEG)[tid] = make_uint4(0, 0, 0, 0);
        if (tid < 32) s_cur[NSLOT + tid] = 0x80000000u;
        if (tid < 8) s_gi[NWG * GPW * 8 + tid] = make_uint2(sb + SM_TBL, xrow0);
        if (MODE & 1) {
#pragma unroll
            for (int j = 0; j < (G * CAPC / 2 + NT - 1) / NT; j++)
                if (tid + NT * j < G * CAPC / 2) reinterpret_cast<uint4*>(sm + SM_TBL)[tid + NT * j] = make_uint4(0, 511, 0, 511);
            if (tw == 0) {
                expect_tx(bar + 8, nvec * 24);
                bulk_load(sb + SM_ENT + wg * VWG * 24, p.src + e0, nvec * 16, bar + 8);
                bulk_load(sb + SM_ENT + wg * VWG * 24 + VWG * 16, p.e + e0, nvec * 8, bar + 8);
            }
        }
        bar_sync<B_EDGE, NT>();

        const uint32_t epoch = (cnt0 >> 10) + (MODE == 2 ? 0 : 1);
        const uint32_t tag5 = epoch << 27, tag23 = epoch << 9;
        if (MODE & 1) {
            int4 dv[VPT];
            mbar_wait(bar);
#pragma unroll
            for (int j = 0; j < VPT; j++) dv[j] = reinterpret_cast<const int4*>(sm + SM_RING + wg * XROWS * 128)[tw + 128 * j];
            uint32_t key[VPT * 4];
#pragma unroll
            for (int j = 0; j < VPT; j++) {
                const bool ok = tw + 128 * j < nvec;
                const int d[4] = {dv[j].x, dv[j].y, dv[j].z, dv[j].w};
#pragma unroll
                for (int q = 0; q < 4; q++) {
                    const uint32_t b = ok ? __umulhi((uint32_t)d[q], p.magic) : G;
                    const uint32_t r = atomicAdd(&s_hist[b], 1u);
                    key[j * 4 + q] = (b * CAPC + min(r, CAPC - 1u)) | ((uint32_t)(d[q] - b * p.npc) << 16);
                }
            }
            proxy_fence();
            bar_sync<B_EDGE, NT>();
            if (tid < G) {
                st_relaxed(p.len + tid * LSTR + cta, min(s_hist[tid], 511u) | tag23);
                if (cta < (-G & 7)) p.len[tid * LSTR + G + cta] = 0;
            }
            mbar_wait(bar + 8);
            load_x();
            uint2* stage = reinterpret_cast<uint2*>(sm + SM_TBL);
            uint32_t emax = 0;
#pragma unroll
            for (int j = 0; j < VPT; j++) {
                const uint4 sv = reinterpret_cast<const uint4*>(sm + SM_ENT + wg * VWG * 24)[tw + 128 * j];
                uint2 ev = reinterpret_cast<const uint2*>(sm + SM_ENT + wg * VWG * 24 + VWG * 16)[tw + 128 * j];
                ev.x = bf2h(ev.x); ev.y = bf2h(ev.y);
                if (tw + 128 * j < nvec) emax = hamax2(emax, hamax2(ev.x, ev.y));
                const uint32_t w0[4] = {__byte_perm(sv.x, ev.x, 0x5410), __byte_perm(sv.y, ev.x, 0x7610),
                                        __byte_perm(sv.z, ev.y, 0x5410), __byte_perm(sv.w, ev.y, 0x7610)};
#pragma unroll
                for (int q = 0; q < 4; q++) stage[key[j * 4 + q] & 0xffff] = make_uint2(w0[q], key[j * 4 + q] >> 16);
            }
            if (hmag(emax) > H_MAX) {
#pragma unroll
                for (int k = 0; k < VPT * 4; k++) stage[key[k] & 0xffff].y = 510;
            }
            bar_sync<B_EDGE, NT>();
            PROF(3);
            {
                const int b = warp + NW * lane;
                const uint32_t c = b < G ? s_hist[b] : 0;
                for (uint32_t m = __ballot_sync(0xffffffffu, c > 3 * CV); m; m &= m - 1) {
                    const int l = __ffs(m) - 1, bl = warp + NW * l;
                    if (3 * CV + (lane & ~3) < __shfl_sync(0xffffffffu, c, l)) {
                        const uint2 v = stage[bl * CAPC + 3 * CV + lane];
                        st_relaxed8(p.ext + (bl * G + cta) * CX + lane, v.x, v.y | tag23);
                    }
                }
            }
            if (tid < BPR * CV) {
                const int xb = tid / CV, xi = tid - xb * CV;
                const uint2* st = stage + xb * CAPC + xi * 3;
                uint4* gc = p.cell + (xb * G + cta) * CV + xi;
                uint4 v[RND];
#pragma unroll
                for (int j = 0; j < RND; j++)
                    if (xb + BPR * j < G) {
                        const uint2 a = st[j * BPR * CAPC], b = st[j * BPR * CAPC + 1], c = st[j * BPR * CAPC + 2];
                        v[j] = make_uint4(a.x, b.x, c.x, a.y + b.y * 512 + c.y * 262144 + tag5);
                    }
#pragma unroll
                for (int j = 0; j < RND; j++)
                    if (xb + BPR * j < G) {
                        st_relaxed16(gc + j * BPR * G * CV, v[j]);
                        if (j == 2 && tid == NT - 32) asm volatile("red.relaxed.gpu.global.add.u32 [%0], %1;" ::"l"(p.cnt), "r"(share) : "memory");
                    }
            }
        }
        if (tid == 0) s_misc[M_EPOCH] = epoch;
        bar_sync<B_SENT, NTA>();
        asm volatile("setmaxnreg.inc.sync.aligned.u32 112;");
        PROF(4);
        {
            mbar_wait(bar + 16);
            uint4* xs = reinterpret_cast<uint4*>(sm + SM_RING + wg * XROWS * 128) + tw;
            uint4 v[XROWS / 16];
            uint32_t mx = 0, my = 0;
#pragma unroll
            for (int j = 0; j < XROWS / 16; j++) v[j] = xs[128 * j];
#pragma unroll
            for (int j = 0; j < XROWS / 16; j++) {
                v[j].x = bf2h(v[j].x); v[j].y = bf2h(v[j].y); v[j].z = bf2h(v[j].z); v[j].w = bf2h(v[j].w);
                xs[128 * j] = v[j];
                mx = hfma2(v[j].x, v[j].x, hfma2(v[j].z, v[j].z, mx));
                my = hfma2(v[j].y, v[j].y, hfma2(v[j].w, v[j].w, my));
            }
            if (hmag(hamax2(mx, my)) > SQ_MAX) s_misc[M_XBAD] = 1;
            if (hmag(hamax2(mx, my)) >= SQ_MIN) s_misc[M_XBIG] = 1;
            proxy_fence();
            if (MODE & 1) bar_arrive<B_CONV, NT + 32>();
            if (!(MODE & 2)) return;
            bar_sync<128>(1 + wg);
        }
        uint32_t da[24], du[24];
        {
            const uint32_t dx = (1u << 16) | ((sb + SM_RING + wg * XROWS * 128) >> 4);
            constexpr uint32_t dw = (1u << 16) | ((sb + SM_W) >> 4);
            wg_fence();
            mma_ss<0>(da, dw, dx);
            mma_ss<0>(du, dw + 512, dx);
#pragma unroll
            for (int k = 1; k < 4; k++) { mma_ss<1>(da, dw + 128 * k, dx + 2 * k); mma_ss<1>(du, dw + 512 + 128 * k, dx + 2 * k); }
            wg_commit();
            wg_wait();
            keep(da); keep(du);
        }
        auto table = [&]() {
            unsigned char* tb = sm + SM_TBL + (wg * XROWS + 2 * t4) * 256 + ((ch * 4) ^ (t4 << 5));
            uint32_t am = 0;
#pragma unroll
            for (int j = 0; j < 12; j++) {
                am = hamax2(am, hamax2(da[2 * j], da[2 * j + 1]));
#pragma unroll
                for (int h = 0; h < 2; h++)
                    if (j < 11 || wg * XROWS + 8 * j + 2 * t4 + h < NROW)
                        *reinterpret_cast<uint2*>(tb + (8 * j + h) * 256) =
                            make_uint2(__byte_perm(da[2 * j], da[2 * j + 1], h ? 0x7632 : 0x5410), __byte_perm(du[2 * j], du[2 * j + 1], h ? 0x7632 : 0x5410));
            }
            if (hmag(am) > A_MAX) s_misc[M_RANGE] = 1;
        };
        if (wg < NWG - 1) table();
        PROF(5);
        uint4 en[RNC];
        uint32_t d4[RNC * 3];
        auto count = [&](int j0, int j1) {
            mbar_wait(sb + SM_LBAR + 4 * j0);
#pragma unroll
            for (int j = j0; j < j1; j++) {
                if (j < RNC - 1 || tid + j * NT < G * CV) en[j] = reinterpret_cast<const uint4*>(sm + (j < 4 ? SM_ENT : SM_LND2 - 2 * LND))[j * NT + tid];
                else en[j] = make_uint4(0, 0, 0, tag5 | 0x7ffffffu);
            }
            for (uint32_t it = 0;; it++) {
                uint32_t miss = 0;
#pragma unroll
                for (int j = j0; j < j1; j++) miss |= en[j].w ^ tag5;
                if (miss < (1u << 27)) break;
#pragma unroll
                for (int j = j0; j < j1; j++)
                    ld_relaxed16_if(en[j], p.cell + cta * G * CV + tid + j * NT, (en[j].w ^ tag5) >= (1u << 27));
                spin_limit(it);
            }
            __syncwarp();
#pragma unroll
            for (int j = j0; j < j1; j++)
#pragma unroll
                for (int s = 0; s < 3; s++) {
                    d4[3 * j + s] = (s == 0 ? en[j].w << 2 : en[j].w >> (9 * s - 2)) & 0x7fc;
                    asm volatile("red.shared.add.u32 [%0+%1], 1;" ::"r"(d4[3 * j + s]), "n"(sb + SM_DEG) : "memory");
                }
        };
        count(0, 2);
        count(2, 4);
        PROF(6);
        count(4, RNC);
        bar_sync<B_COUNT, NT + 96>();
        PROF(7);
        uint32_t unused = 0;
        if (warp < NSLOT / 32) {
            const uint32_t dg = s_deg[tid];
            if (dg > 62 || s_deg[510] || xrow0 > ~0u - NSLOT * 128 || (uint32_t)oa > ~0u - NSLOT * 128) s_misc[M_NOFIT] = 1;
            const uint32_t kb = tid < nvalid ? 62 - min(dg, 62u) : 63;
            const uint32_t r = atomicAdd(&s_dh[kb], 1u);
            bar_sync<B_NODE, NSLOT>();
            const uint2 h = reinterpret_cast<const uint2*>(s_dh)[lane];
            uint32_t inc = h.x + h.y;
#pragma unroll
            for (int o = 1; o < 32; o <<= 1) { const uint32_t v = __shfl_up_sync(0xffffffffu, inc, o); if (lane >= o) inc += v; }
            const uint32_t pe = __shfl_sync(0xffffffffu, inc - h.x - h.y, kb >> 1), po = __shfl_sync(0xffffffffu, inc - h.y, kb >> 1);
            const uint32_t pos = ((kb & 1) ? po : pe) + r;
            const uint32_t grp = pos >> 3, slot = pos & 7, row = grp / NWG, col = grp - row * NWG;
            const uint32_t seg = (row & 1) ? NWG - 1 - col : col;
            const uint32_t idx = seg * GPW + GPW - 1 - row;
            if (slot == 0) s_lg[idx] = max(dg, (uint32_t)NSTEP);
            bar_sync<B_NODE, NSLOT>();
            const uint2 l = reinterpret_cast<const uint2*>(s_lg)[lane];
            uint32_t in2 = l.x + l.y;
#pragma unroll
            for (int o = 1; o < 32; o <<= 1) { const uint32_t v = __shfl_up_sync(0xffffffffu, in2, o); if (lane >= o) in2 += v; }
            const uint32_t ex2 = in2 - l.x - l.y;
            const uint32_t mine = __shfl_sync(0xffffffffu, ex2, (lane / (GPW / 2)) * (GPW / 2));
            const uint32_t ee = __shfl_sync(0xffffffffu, in2 - l.y, idx >> 1), eo = __shfl_sync(0xffffffffu, in2, idx >> 1);
            const uint32_t sbeg = __shfl_sync(0xffffffffu, ex2, seg * (GPW / 2));
            if (__any_sync(0xffffffffu, in2 > CAP / 8 || in2 - mine > MAXT * NSTEP) || s_misc[M_NOFIT] != 0) {
                s_misc[M_SKIP] = 1;
            } else {
                const uint32_t gend = (idx & 1) ? eo : ee;
                s_cur[tid] = (gend - dg) * 32 + slot * 4;
                if (tid < nvalid) s_gi[idx * 8 + slot] = make_uint2(sb + SM_TBL + tid * 256 + (((tid >> 1) & 3) << 5), xrow0 + tid * 128);
                else unused = (idx * 8 + slot) | ((seg * GPW + GPW - 1) * 8 + slot) << 16;
                if (slot == 0) {
                    const uint32_t last = gend - 1 - sbeg;
                    s_end[seg * MAXT + last / NSTEP] = last % NSTEP + 1;
                }
                if (tid <= NWG * (GPW / 2) && tid % (GPW / 2) == 0) s_misc[M_STEP0 + tid / (GPW / 2)] = ex2;
            }
        } else {
            table();
        }
        bar_sync<B_SORT, NT + 96>();
        PROF(8);
        if (s_misc[M_SKIP] == 0) {
            if (unused) { const uint2 v = s_gi[unused >> 16]; s_gi[unused & 0xffff] = make_uint2(v.x ^ 8, v.y); }
            auto place = [&](int j1) {
#pragma unroll
                for (int k = 0; k < 3 * j1; k++)
                    asm volatile("atom.shared.add.u32 %0, [%1+%2], 32;" : "=r"(d4[k]) : "r"(min(d4[k], (NSLOT + lane) * 4u)), "n"(sb + SM_CUR) : "memory");
#pragma unroll
                for (int j = 0; j < j1; j++)
#pragma unroll
                    for (int s = 0; s < 3; s++)
                        asm volatile("{\n.reg .pred q;\nsetp.ge.s32 q, %0, 0;\n@q st.shared.u32 [%0+%2], %1;\n}"
                                     ::"r"(d4[3 * j + s]), "r"(s == 0 ? en[j].x : s == 1 ? en[j].y : en[j].z), "n"(sb + SM_ENT));
            };
            if (warp * 32 + (RNC - 1) * NT < G * CV) place(RNC); else place(RNC - 1);
        }
        __syncthreads();
        PROF(9);
        uint32_t plain = s_misc[M_SKIP] | s_misc[M_RANGE] | (s_misc[M_XBIG] ^ 1);
        if (!plain) {
            __nanosleep(wg * 120);
            uint32_t fb[16], fv[16], fe[4];
            {
                const uint32_t a = sb + SM_W + 16384 + ((lane >> 4) * 8 + (lane & 7)) * 128 + (((2 * w4 + ((lane >> 3) & 1)) ^ (lane & 7)) << 4);
#pragma unroll
                for (int k = 0; k < 4; k++) {
                    ldsm_t(fb + 4 * k, a + k * 2048);
                    ldsm_t(fv + 4 * k, a + 8192 + k * 2048);
                }
                const uint32_t wh = reinterpret_cast<const uint32_t*>(sm + SM_WC)[ch >> 1];
                fe[0] = t4 != wg ? 0 : __byte_perm(wh, 0xfb53, 0x5410);
                fe[1] = t4 != wg ? 0 : __byte_perm(wh, 0xfb53, 0x5432);
                fe[2] = fe[3] = 0;
            }
            const uint32_t step0 = __shfl_sync(0xffffffffu, s_misc[M_STEP0 + wg], 0);
            const uint32_t T = (__shfl_sync(0xffffffffu, s_misc[M_STEP0 + 1 + wg], 0) - step0 + NSTEP - 1) / NSTEP;
            uint32_t dx = (1u << 16) | ((sb + SM_RING + wg * (2 * TB)) >> 4);
            uint32_t de = (1u << 16) | ((sb + SM_EXT) >> 4);
            uint32_t ma = sb + SM_END + wg * MAXT * 4;
            uint32_t gptr = opaque32(sb + SM_GI + wg * GPW * 64 + t4 * 16);
            auto pin = [&](uint32_t v) { return __shfl_sync(0xffffffffu, v + lane, lane) - lane; };
            const uint32_t tb4 = pin(ch * 4), chx = pin(ch * 2), cho = pin(ch * 2 + (uint32_t)oa - xrow0);
            uint64_t px[2], po[2];
#pragma unroll
            for (int h = 0; h < 2; h++) {
                px[h] = (uint64_t)(pin((uint32_t)(xa >> 32) + h) - h) << 32;
                po[h] = (uint64_t)(pin((uint32_t)(oa >> 32) + h) - h) << 32;
            }
            const uint32_t turn = pin(1 + wg), next = pin(1 + ((wg + 1) & 3));
            uint32_t flags = 0;
#pragma unroll 1
            for (int row = GPW - 1; (row + 1) * NWG * 8 > nvalid; row--) {
                const int pos = (row * NWG + ((row & 1) ? NWG - 1 - wg : wg)) * 8 + 2 * t4;
                flags |= ((pos + 1 >= nvalid ? 1u : 0u) | (pos >= nvalid ? 0x10000u : 0u)) << (GPW - 1 - row);
            }
            auto set_lo = [&](uint64_t& a, uint32_t r, uint32_t c) {
                asm("{\n.reg .b32 lo, hi;\nmov.b64 {lo, hi}, %0;\nadd.u32 lo, %1, %2;\nmov.b64 %0, {lo, hi};\n}" : "+l"(a) : "r"(r), "r"(c));
            };
            uint32_t hN[2], hD[2], hA[2], u2[2], x2[2] = {0, 0}, zmax = 0;
            uint4 gi;
            uint2 t0, t1;
            auto fetch_group = [&]() {
                gi = lds128(gptr);
                gptr += 64;
                t0 = lds64(gi.x ^ tb4); t1 = lds64(gi.z ^ tb4);
            };
            auto next_a = [&]() {
                const uint32_t a0 = __byte_perm(t0.x, t1.x, 0x5410), a1 = __byte_perm(t0.x, t1.x, 0x7632);
                hA[0] = hsub2(a0, fe[2]); hA[1] = hsub2(a1, fe[3]);
                fe[2] = a0; fe[3] = a1;
            };
            auto next_rows = [&]() {
                set_lo(px[0], gi.y, chx); set_lo(px[1], gi.w, chx);
                set_lo(po[0], gi.y, cho); set_lo(po[1], gi.w, cho);
                u2[0] = __byte_perm(t0.y, t1.y, 0x5410); u2[1] = __byte_perm(t0.y, t1.y, 0x7632);
            };
            auto flush_group = [&](const uint32_t (&hN)[2], const uint32_t (&hD)[2]) {
                uint32_t z[2];
#pragma unroll
                for (int r = 0; r < 2; r++) {
                    const float d0 = h_lo(hD[r]), d1 = h_hi(hD[r]);
                    const float rr = rcp(d0 * d1);
                    uint32_t r2;
                    asm("cvt.rn.satfinite.f16x2.f32 %0, %1, %2;" : "=r"(r2) : "f"(rr * d0), "f"(rr * d1));
                    z[r] = hfma2(hN[r], r2, u2[r]);
                }
                const uint32_t o0 = finish2(h_lo(z[0]), h_lo(z[1]), x2[0]), o1 = finish2(h_hi(z[0]), h_hi(z[1]), x2[1]);
                asm volatile("st.global.u32 [%0], %1;" ::"l"(po[0]), "r"(o0) : "memory");
                asm volatile("st.global.u32 [%0], %1;" ::"l"(po[1]), "r"(o1) : "memory");
                zmax = hamax2(zmax, hamax2(z[0], z[1]));
                flags = __funnelshift_r(flags, flags, 1) ^ (~(__vminu2(hD[0], hD[1]) + (0x80008000u - DEN_SMALL)) & 0x80008000u);
            };
            auto gate = [&](uint32_t g) { return pack_h(1.f + tanh_(h_lo(g)), 1.f + tanh_(h_hi(g))); };
            uint32_t db[2 * NSTEP], dv[2 * NSTEP];
            fetch_group();
            next_a();
            next_rows();
            hN[0] = hN[1] = 0; hD[0] = hD[1] = DEN0;
            if (wg == NWG - 1) bar_arrive<1, 288>();
            const uint32_t mend = ma + 4 * T;
#pragma unroll 1
            while (ma != mend) {
                uint32_t m;
                asm volatile("ld.shared.u32 %0, [%1];" : "=r"(m) : "r"(ma));
                ma += 4;
                bar_sync<288>(turn);
                wg_fence();
                mma_rs<0, 0>(dv, fv, dx);
                mma_rs<0, 0>(db, fb, dx);
#pragma unroll
                for (int k = 1; k < 4; k++) {
                    mma_rs<1, 0>(dv, fv + 4 * k, dx + 2 * k);
                    mma_rs<1, 0>(db, fb + 4 * k, dx + 2 * k);
                }
                mma_rs<1, 1>(db, fe, de);
                wg_commit();
                dx ^= TB >> 4;
                de ^= 128;
                auto block = [&](int e) {
                    bar_arrive<288>(next);
                    if (e > 0) {
                        asm volatile("ld.global.nc.u32 %0, [%1];" : "=r"(x2[0]) : "l"(px[0]));
                        asm volatile("ld.global.nc.u32 %0, [%1];" : "=r"(x2[1]) : "l"(px[1]));
                        fetch_group();
                    }
                    wg_wait();
                    keep(dv); keep(db); keep(fe);
                    if (e > 0) next_a();
                    uint32_t oN[2], oD[2];
#pragma unroll
                    for (int j = 0; j < NSTEP; j++) {
#pragma unroll
                        for (int r = 0; r < 2; r++) {
                            const uint32_t w = gate(e > 0 && j >= e ? hadd2(db[2 * j + r], hA[r]) : db[2 * j + r]);
                            hN[r] = hfma2(w, dv[2 * j + r], hN[r]);
                            hD[r] = hadd2(w, hD[r]);
                        }
                        if (j + 1 == e) {
                            oN[0] = hN[0]; oN[1] = hN[1]; oD[0] = hD[0]; oD[1] = hD[1];
                            hN[0] = hN[1] = 0; hD[0] = hD[1] = DEN0;
                        }
                    }
                    if (e > 0) { flush_group(oN, oD); next_rows(); }
                };
                if (m == 0) block(0);
                else if (m > 4) { if (m > 6) { if (m > 7) block(8); else block(7); } else { if (m > 5) block(6); else block(5); } }
                else { if (m > 2) { if (m > 3) block(4); else block(3); } else { if (m > 1) block(2); else block(1); } }
            }
            PROF(10);
            for (uint32_t i = T, n = max_tiles(); i < n; i++) {
                bar_sync<288>(turn);
                bar_arrive<288>(next);
            }
            if (wg == 0) bar_sync<1, 288>();
            if (__any_sync(0xffffffffu, flags != 0)) redo_small(p.x, p.wb, p.wv, p.wc, p.out, flags, wg, node0);
            asm volatile("{\n.reg .pred q;\nsetp.ge.u32 q, %1, 0x7c00;\nbar.red.or.pred q, %2, %3, q;\nselp.u32 %0, 1, 0, q;\n}"
                         : "=r"(plain) : "r"(hmag(zmax)), "n"((int)B_FINAL), "n"(NT) : "memory");
        }
        if (plain) slow_bin(p, sm, node0, nvalid);
        PROF(14);
    }
}

typedef CUresult (*EncodeFn)(CUtensorMap*, CUtensorMapDataType, cuuint32_t, void*, const cuuint64_t*, const cuuint64_t*,
                             const cuuint32_t*, const cuuint32_t*, CUtensorMapInterleave, CUtensorMapSwizzle,
                             CUtensorMapL2promotion, CUtensorMapFloatOOBfill);

}

extern "C" void kernel_launch(void* const* d_in, const int* in_sizes, int n_in, void* d_out, int out_size) {
    static int sms = 0;
    static EncodeFn encode = nullptr;
    static void *cell = nullptr, *ext = nullptr, *cnt = nullptr, *x16 = nullptr, *len = nullptr;
    if (!sms) {
        int dev = 0;
        cudaGetDevice(&dev);
        cudaDeviceGetAttribute(&sms, cudaDevAttrMultiProcessorCount, dev);
        cudaFuncSetAttribute(gatedgcn_kernel<1>, cudaFuncAttributeMaxDynamicSharedMemorySize, SM_TOTAL);
        cudaFuncSetAttribute(gatedgcn_kernel<2>, cudaFuncAttributeMaxDynamicSharedMemorySize, SM_TOTAL);
        cudaFuncSetAttribute(gatedgcn_kernel<3>, cudaFuncAttributeMaxDynamicSharedMemorySize, SM_TOTAL);
        cudaDriverEntryPointQueryResult qr;
        cudaGetDriverEntryPoint("cuTensorMapEncodeTiled", (void**)&encode, cudaEnableDefault, &qr);
        cudaGetSymbolAddress(&cell, g_cell);
        cudaGetSymbolAddress(&ext, g_ext);
        cudaGetSymbolAddress(&cnt, g_cnt);
        cudaGetSymbolAddress(&len, g_len);
        cudaGetSymbolAddress(&x16, g_x16);
        if (((uint64_t)x16 >> 32) != (((uint64_t)x16 + G * NSLOT * 128 - 1) >> 32)) x16 = (char*)x16 + G * NSLOT * 128;
    }
    Params p;
    p.x = (const __nv_bfloat16*)d_in[0];
    p.e = (const __nv_bfloat16*)d_in[1];
    p.src = (const int*)d_in[2];
    p.dst = (const int*)d_in[3];
    p.wa = (const __nv_bfloat16*)d_in[4];
    p.wb = (const __nv_bfloat16*)d_in[5];
    p.wc = (const __nv_bfloat16*)d_in[6];
    p.wu = (const __nv_bfloat16*)d_in[7];
    p.wv = (const __nv_bfloat16*)d_in[8];
    p.out = (__nv_bfloat16*)d_out;
    p.cell = (uint4*)cell;
    p.ext = (uint64_t*)ext;
    p.len = (uint32_t*)len;
    p.cnt = (uint32_t*)cnt;
    p.x16 = (const uint4*)x16;
    p.N = in_sizes[0] / 64;
    p.E = in_sizes[2];
    p.npc = (p.N + G - 1) / G;
    p.chunk = ((p.E + G - 1) / G + 7) & ~7;
    p.magic = (uint32_t)(0x100000000ull / (uint32_t)p.npc) + 1u;
    if (!encode || p.npc > NROW || p.N - (G - 1) * p.npc < 8 * NWG || p.chunk > CHUNK_MAX || (p.E & 7) ||
        p.E - (G - 1) * p.chunk <= (NWG - 1) * VWG * 4) return;

    CUtensorMap xmap, hmap;
    const cuuint64_t dims[2] = {64, (cuuint64_t)p.N};
    const cuuint64_t strides[1] = {128};
    const cuuint32_t box[2] = {64, XROWS}, estr[2] = {1, 1};
    encode(&xmap, CU_TENSOR_MAP_DATA_TYPE_BFLOAT16, 2, d_in[0], dims, strides, box, estr, CU_TENSOR_MAP_INTERLEAVE_NONE,
           CU_TENSOR_MAP_SWIZZLE_128B, CU_TENSOR_MAP_L2_PROMOTION_L2_256B, CU_TENSOR_MAP_FLOAT_OOB_FILL_NONE);
    encode(&hmap, CU_TENSOR_MAP_DATA_TYPE_FLOAT16, 2, x16, dims, strides, box, estr, CU_TENSOR_MAP_INTERLEAVE_NONE,
           CU_TENSOR_MAP_SWIZZLE_128B, CU_TENSOR_MAP_L2_PROMOTION_NONE, CU_TENSOR_MAP_FLOAT_OOB_FILL_NONE);
    if (sms >= G) {
        gatedgcn_kernel<3><<<G, NTA, SM_TOTAL>>>(p, xmap, hmap);
    } else {
        gatedgcn_kernel<1><<<G, NTA, SM_TOTAL>>>(p, xmap, hmap);
        gatedgcn_kernel<2><<<G, NTA, SM_TOTAL>>>(p, xmap, hmap);
    }
}
```

```cpp
#include <cuda_runtime.h>
#include <cuda_bf16.h>
#include <cuda_fp16.h>
#include <cuda.h>
#include <stdint.h>

namespace {

constexpr int G = 132;
constexpr int NWG = 4;
constexpr int NT = NWG * 128;
constexpr int NW = NT / 32;
constexpr int NTA = NT + 128;
constexpr int NSLOT = 384;
constexpr int NROW = 380;
constexpr int GPW = NSLOT / 8 / NWG;
constexpr int XROWS = NSLOT / NWG;
constexpr int VPT = 3;
constexpr int VWG = 128 * VPT;
constexpr int CHUNK_MAX = NT * VPT * 4;
constexpr int CV = 18;
constexpr int CX = 32;
constexpr int CAPC = 3 * CV + CX;
constexpr int LSTR = 160;
constexpr int BPR = NT / CV;
constexpr int RND = (G + BPR - 1) / BPR;
constexpr int RNC = (G * CV + NT - 1) / NT;
constexpr int TPL = 4;
constexpr int NSTEP = 8;
constexpr int TB = NSTEP * 8 * 128;
constexpr int CAP = 6784;
constexpr int CAPX = CAP + NSTEP * 8;
constexpr int MAXT = 40;
static_assert(GPW % 2 == 0 && GPW <= 16 && G % 3 == 0 && G <= 192 && RNC == 5, "layout");

constexpr uint32_t SB = 1024;
constexpr int SM_RING = 0;
constexpr int SM_W = SM_RING + NSLOT * 128;
constexpr int SM_TBL = SM_W + 4 * 8192;
constexpr int SM_ENT = SM_TBL + NROW * 256;
constexpr int SM_EXT = SM_ENT + CHUNK_MAX * 6;
constexpr int SM_DEG = SM_EXT + 4096;
constexpr int SM_DH = SM_DEG + 512 * 4;
constexpr int SM_LG = SM_DH + 64 * 4;
constexpr int SM_END = SM_LG + 64 * 4;
constexpr int SM_MISC = SM_END + NWG * MAXT * 4;
constexpr int SM_HIST = SM_MISC + 64;
constexpr int SM_CUR = SM_HIST + 144 * 4;
constexpr int SM_GI = SM_CUR + 512 * 4;
constexpr int SM_BAR = SM_GI + (NWG * GPW + 1) * 64;
constexpr int SM_LBAR = SM_BAR + 96;
constexpr int SM_WC = SM_LBAR + 32;
constexpr int SM_TOTAL = SM_WC + 128;
constexpr int LND = 2 * NT * 16;
constexpr int SM_LND2 = SM_TBL + (NWG - 1) * XROWS * 256;
static_assert(SM_TOTAL <= 232448 && NSLOT * 128 * 4 <= SM_DEG, "smem");
static_assert(NWG * 2 * TB <= SM_W + 16384 && SM_TBL % 1024 == 0 && SM_EXT % 1024 == 0 && (SB + SM_EXT) % 4096 < 2048, "align");
static_assert((G + 1) * CAPC * 8 <= NROW * 256 && CAPC % 2 == 0, "outgoing cells");
static_assert(CAPX * 4 <= CHUNK_MAX * 6 && 2 * LND <= CHUNK_MAX * 6 && SM_LND2 + G * CV * 16 - 2 * LND <= SM_ENT, "aliases");
static_assert(SM_CUR % 16 == 0 && SM_GI % 16 == 0 && SM_WC % 16 == 0, "vector access");
enum { M_NOFIT, M_LATE, M_XBIG, M_XBAD, M_RANGE, M_SKIP, M_EPOCH, M_STEP0 = 8 };
enum { B_EDGE = 6, B_NODE, B_SENT, B_FINAL, B_CONV, B_COUNT, B_READY, B_SORT, B_GO, B_ROWS };

__device__ __align__(128) uint4 g_cell[G * G * CV];
__device__ __align__(128) uint64_t g_ext[G * G * CX];
__device__ __align__(128) uint32_t g_len[G * LSTR];
__device__ __align__(128) uint4 g_x16[2 * G * NSLOT * 8];
__device__ __align__(128) uint32_t g_cnt[64];
#define PROFT(i, t)
#define PROF(i) PROFT(i, 0)

constexpr uint32_t DEN0 = 0x00220022u;
constexpr uint32_t DEN_SMALL = 0x03470347u;
constexpr uint32_t E_PAD = 0xffff0000u;
constexpr uint32_t H_MAX = 0x4ff0u;
constexpr uint32_t A_MAX = 0x5000u;
constexpr uint32_t SQ_MAX = 0x6380u;
constexpr uint32_t SQ_MIN = 0x2240u;

__device__ __forceinline__ float tanh_(float x) { float y; asm("tanh.approx.f32 %0, %1;" : "=f"(y) : "f"(x)); return y; }
__device__ __forceinline__ float rcp(float x) { float y; asm("rcp.approx.ftz.f32 %0, %1;" : "=f"(y) : "f"(x)); return y; }
__device__ __forceinline__ uint32_t pack_bf16(float lo, float hi) { uint32_t r; asm("cvt.rn.bf16x2.f32 %0, %1, %2;" : "=r"(r) : "f"(hi), "f"(lo)); return r; }
__device__ __forceinline__ uint32_t pack_h(float lo, float hi) { uint32_t r; asm("cvt.rn.f16x2.f32 %0, %1, %2;" : "=r"(r) : "f"(hi), "f"(lo)); return r; }
__device__ __forceinline__ float h_lo(uint32_t v) { return __low2float(*reinterpret_cast<__half2*>(&v)); }
__device__ __forceinline__ float h_hi(uint32_t v) { return __high2float(*reinterpret_cast<__half2*>(&v)); }
__device__ __forceinline__ uint32_t hadd2(uint32_t a, uint32_t b) { uint32_t r; asm("add.rn.f16x2 %0, %1, %2;" : "=r"(r) : "r"(a), "r"(b)); return r; }
__device__ __forceinline__ uint32_t hsub2(uint32_t a, uint32_t b) { uint32_t r; asm("sub.rn.f16x2 %0, %1, %2;" : "=r"(r) : "r"(a), "r"(b)); return r; }
__device__ __forceinline__ uint32_t hfma2(uint32_t a, uint32_t b, uint32_t c) { uint32_t r; asm("fma.rn.f16x2 %0, %1, %2, %3;" : "=r"(r) : "r"(a), "r"(b), "r"(c)); return r; }
__device__ __forceinline__ uint32_t hamax2(uint32_t a, uint32_t b) { uint32_t r; asm("max.NaN.xorsign.abs.f16x2 %0, %1, %2;" : "=r"(r) : "r"(a), "r"(b)); return r; }
__device__ __forceinline__ uint32_t hmag(uint32_t m) { return max(m & 0x7fffu, (m >> 16) & 0x7fffu); }
__device__ __forceinline__ float bf_lo(uint32_t v) { return __uint_as_float(v << 16); }
__device__ __forceinline__ float bf_hi(uint32_t v) { return __uint_as_float(v & 0xffff0000u); }
__device__ __forceinline__ uint32_t bf2h(uint32_t v) { return pack_h(bf_lo(v), bf_hi(v)); }
__device__ __forceinline__ uint32_t finish2(float z0, float z1, uint32_t x) {
    uint32_t z, o;
    asm("cvt.rn.relu.bf16x2.f32 %0, %1, %2;" : "=r"(z) : "f"(z1), "f"(z0));
    asm("fma.rn.bf16x2 %0, %1, %2, %3;" : "=r"(o) : "r"(z), "r"(0x3b803b80u), "r"(x));
    return o;
}
__device__ __forceinline__ uint32_t opaque32(uint32_t v) { asm volatile("" : "+r"(v)); return v; }
__device__ __forceinline__ uint2 lds64(uint32_t a) { uint2 v; asm volatile("ld.shared.v2.u32 {%0,%1}, [%2];" : "=r"(v.x), "=r"(v.y) : "r"(a)); return v; }
__device__ __forceinline__ uint4 lds128(uint32_t a) {
    uint4 v;
    asm("ld.shared.v4.u32 {%0,%1,%2,%3}, [%4];" : "=r"(v.x), "=r"(v.y), "=r"(v.z), "=r"(v.w) : "r"(a));
    return v;
}

__device__ __forceinline__ void spin_limit(uint32_t it) {
    asm volatile("{\n.reg .pred q;\n.reg .b64 z;\nmov.b64 z, 0;\nsetp.gt.u32 q, %0, 0x400000;\n@q st.global.u32 [z], %0;\n}" ::"r"(it));
}
__device__ __forceinline__ void wg_fence() { asm volatile("wgmma.fence.sync.aligned;" ::: "memory"); }
__device__ __forceinline__ void wg_commit() { asm volatile("wgmma.commit_group.sync.aligned;" ::: "memory"); }
__device__ __forceinline__ void wg_wait() { asm volatile("wgmma.wait_group.sync.aligned 0;" ::: "memory"); }
__device__ __forceinline__ void proxy_fence() { asm volatile("fence.proxy.async.shared::cta;" ::: "memory"); }
__device__ __forceinline__ void cp_commit() { asm volatile("cp.async.commit_group;" ::: "memory"); }
__device__ __forceinline__ void cp_wait() { asm volatile("cp.async.wait_group 0;" ::: "memory"); }
__device__ __forceinline__ void cp16(uint32_t dst, const void* src) { asm volatile("cp.async.cg.shared.global [%0], [%1], 16;" ::"r"(dst), "l"(src) : "memory"); }
template <int ID, int N> __device__ __forceinline__ void bar_sync() { asm volatile("bar.sync %0, %1;" ::"n"(ID), "n"(N) : "memory"); }
template <int ID, int N> __device__ __forceinline__ void bar_arrive() { asm volatile("bar.arrive %0, %1;" ::"n"(ID), "n"(N) : "memory"); }
template <int N> __device__ __forceinline__ void bar_sync(uint32_t id) { asm volatile("bar.sync %0, %1;" ::"r"(id), "n"(N) : "memory"); }
template <int N> __device__ __forceinline__ void bar_arrive(uint32_t id) { asm volatile("bar.arrive %0, %1;" ::"r"(id), "n"(N) : "memory"); }
__device__ __forceinline__ uint32_t ld_relaxed(const uint32_t* p) {
    uint32_t v;
    asm volatile("ld.relaxed.gpu.global.u32 %0, [%1];" : "=r"(v) : "l"(p) : "memory");
    return v;
}
__device__ __forceinline__ void st_relaxed(uint32_t* p, uint32_t v) { asm volatile("st.relaxed.gpu.global.u32 [%0], %1;" ::"l"(p), "r"(v) : "memory"); }
__device__ __forceinline__ uint2 ld_relaxed8(const void* p) {
    uint2 v;
    asm volatile("{\n.reg .b64 t;\nld.relaxed.gpu.global.b64 t, [%2];\nmov.b64 {%0, %1}, t;\n}" : "=r"(v.x), "=r"(v.y) : "l"(p) : "memory");
    return v;
}
__device__ __forceinline__ void st_relaxed8(void* p, uint32_t lo, uint32_t hi) {
    asm volatile("{\n.reg .b64 t;\nmov.b64 t, {%1, %2};\nst.relaxed.gpu.global.b64 [%0], t;\n}" ::"l"(p), "r"(lo), "r"(hi) : "memory");
}
__device__ __forceinline__ void bulk_load(uint32_t dst, const void* src, uint32_t bytes, uint32_t bar) {
    asm volatile("cp.async.bulk.shared::cluster.global.mbarrier::complete_tx::bytes [%0], [%1], %2, [%3];"
                 ::"r"(dst), "l"(src), "r"(bytes), "r"(bar) : "memory");
}
__device__ __forceinline__ void mbar_init(uint32_t bar) { asm volatile("mbarrier.init.shared::cta.b64 [%0], 1;" ::"r"(bar) : "memory"); }
__device__ __forceinline__ void expect_tx(uint32_t bar, uint32_t bytes) {
    asm volatile("mbarrier.arrive.expect_tx.shared::cta.b64 _, [%0], %1;" ::"r"(bar), "r"(bytes) : "memory");
}
__device__ __forceinline__ bool mbar_try(uint32_t bar) {
    uint32_t ok;
    asm volatile("{\n.reg .pred q;\nmbarrier.try_wait.parity.shared::cta.b64 q, [%1], 0;\nselp.u32 %0, 1, 0, q;\n}"
                 : "=r"(ok) : "r"(bar) : "memory");
    return ok;
}
__device__ __forceinline__ void mbar_wait(uint32_t bar) {
    for (uint32_t it = 0; !mbar_try(bar); it++) spin_limit(it);
}
__device__ __forceinline__ void ld_relaxed16_if(uint4& v, const uint4* p, bool on) {
    asm volatile("{\n.reg .pred q;\n.reg .b128 t;\n.reg .b64 a, b;\nsetp.ne.u32 q, %5, 0;\n"
                 "mov.b64 a, {%0, %1};\nmov.b64 b, {%2, %3};\nmov.b128 t, {a, b};\n@q ld.relaxed.gpu.global.b128 t, [%4];\n"
                 "mov.b128 {a, b}, t;\nmov.b64 {%0, %1}, a;\nmov.b64 {%2, %3}, b;\n}"
                 : "+r"(v.x), "+r"(v.y), "+r"(v.z), "+r"(v.w) : "l"(p), "r"((uint32_t)on) : "memory");
}
__device__ __forceinline__ void st_relaxed16(uint4* p, uint4 v) {
    asm volatile("{\n.reg .b128 t;\n.reg .b64 a, b;\nmov.b64 a, {%1, %2};\nmov.b64 b, {%3, %4};\nmov.b128 t, {a, b};\n"
                 "st.relaxed.gpu.global.b128 [%0], t;\n}"
                 ::"l"(p), "r"(v.x), "r"(v.y), "r"(v.z), "r"(v.w) : "memory");
}

#define R4(d, o) "+r"(d[o]), "+r"(d[o + 1]), "+r"(d[o + 2]), "+r"(d[o + 3])
#define L16 "%0,%1,%2,%3,%4,%5,%6,%7,%8,%9,%10,%11,%12,%13,%14,%15"
#define L24 L16 ",%16,%17,%18,%19,%20,%21,%22,%23"
constexpr uint32_t HI_SW = 0x40000000u | 64u;
template <int A>
__device__ __forceinline__ void mma_ss(uint32_t (&d)[24], uint32_t alo, uint32_t blo) {
    asm volatile("{\n.reg .b64 a, b;\nmov.b64 a, {%24, %26};\nmov.b64 b, {%25, %26};\n"
                 "wgmma.mma_async.sync.aligned.m64n96k16.f16.f16.f16 {" L24 "}, a, b, %27, 1, 1, 1, 0;\n}\n"
                 : R4(d, 0), R4(d, 4), R4(d, 8), R4(d, 12), R4(d, 16), R4(d, 20)
                 : "r"(alo), "r"(blo), "r"(HI_SW), "n"(A));
}
template <int A, int T>
__device__ __forceinline__ void mma_rs(uint32_t (&d)[16], const uint32_t* a, uint32_t blo) {
    asm volatile("{\n.reg .b64 b;\nmov.b64 b, {%20, %21};\n"
                 "wgmma.mma_async.sync.aligned.m64n64k16.f16.f16.f16 {" L16 "}, {%16,%17,%18,%19}, b, %22, 1, 1, %23;\n}\n"
                 : R4(d, 0), R4(d, 4), R4(d, 8), R4(d, 12)
                 : "r"(a[0]), "r"(a[1]), "r"(a[2]), "r"(a[3]), "r"(blo), "r"(HI_SW), "n"(A), "n"(T));
}
template <int R> __device__ __forceinline__ void keep(uint32_t (&d)[R]) {
#pragma unroll
    for (int i = 0; i < R; i++) asm volatile("" : "+r"(d[i])::"memory");
}
__device__ __forceinline__ void ldsm_t(uint32_t* f, uint32_t addr) {
    asm volatile("ldmatrix.sync.aligned.m8n8.x4.trans.shared.b16 {%0,%1,%2,%3}, [%4];"
                 : "=r"(f[0]), "=r"(f[1]), "=r"(f[2]), "=r"(f[3]) : "r"(addr) : "memory");
}
__device__ __forceinline__ uint32_t stage_w(unsigned char* mat, int k, int c, uint4 a, uint4 b, float s) {
    unsigned char* row = mat + k * 128;
    const uint4 e = make_uint4(pack_h(s * bf_lo(a.x), s * bf_lo(a.y)), pack_h(s * bf_lo(a.z), s * bf_lo(a.w)),
                               pack_h(s * bf_lo(b.x), s * bf_lo(b.y)), pack_h(s * bf_lo(b.z), s * bf_lo(b.w)));
    const uint4 o = make_uint4(pack_h(s * bf_hi(a.x), s * bf_hi(a.y)), pack_h(s * bf_hi(a.z), s * bf_hi(a.w)),
                               pack_h(s * bf_hi(b.x), s * bf_hi(b.y)), pack_h(s * bf_hi(b.z), s * bf_hi(b.w)));
    *reinterpret_cast<uint4*>(row + ((c ^ (k & 7)) << 4)) = e;
    *reinterpret_cast<uint4*>(row + (((c + 1) ^ (k & 7)) << 4)) = o;
    return hamax2(hamax2(hamax2(e.x, e.y), hamax2(e.z, e.w)), hamax2(hamax2(o.x, o.y), hamax2(o.z, o.w)));
}

struct Params {
    const int* dst;
    const int* src;
    const __nv_bfloat16* e;
    int N, E, npc, chunk;
    const __nv_bfloat16* x;
    __nv_bfloat16* out;
    uint32_t* cnt;
    const __nv_bfloat16 *wa, *wb, *wc, *wu, *wv;
    uint4* cell;
    uint64_t* ext;
    uint32_t* len;
    const uint4* x16;
    uint32_t magic;
};

__device__ __noinline__ void slow_bin(const Params& p, unsigned char* sm, int node0, int nvalid) {
    float* acc = reinterpret_cast<float*>(sm);
    const int tid = threadIdx.x, lane = tid & 31, warp = tid >> 5;
    bar_sync<B_EDGE, NT>();
    for (int i = tid; i < NSLOT * 128; i += NT) acc[i] = 0.f;
    bar_sync<B_EDGE, NT>();
    const uint32_t* x2 = reinterpret_cast<const uint32_t*>(p.x);
    const uint32_t* wb = reinterpret_cast<const uint32_t*>(p.wb) + lane;
    const uint32_t* wv = reinterpret_cast<const uint32_t*>(p.wv) + lane;
    const uint32_t* wa = reinterpret_cast<const uint32_t*>(p.wa) + lane;
    const uint32_t* wu = reinterpret_cast<const uint32_t*>(p.wu) + lane;
    const uint32_t wc = reinterpret_cast<const uint32_t*>(p.wc)[lane];
    for (int i0 = warp * 32; i0 < p.E; i0 += NT) {
        const int dl = i0 + lane < p.E ? p.dst[i0 + lane] - node0 : -1;
        uint32_t m = __ballot_sync(0xffffffffu, (uint32_t)dl < (uint32_t)nvalid);
        while (m) {
            const int l = __ffs(m) - 1;
            m &= m - 1;
            const int d = __shfl_sync(0xffffffffu, dl, l);
            const uint32_t xs = x2[p.src[i0 + l] * 32 + lane], xd = x2[(node0 + d) * 32 + lane];
            float g0 = 0.f, g1 = 0.f, v0 = 0.f, v1 = 0.f;
#pragma unroll 4
            for (int k = 0; k < 32; k++) {
                const uint32_t a = __shfl_sync(0xffffffffu, xs, k), b = __shfl_sync(0xffffffffu, xd, k);
#pragma unroll
                for (int h = 0; h < 2; h++) {
                    const float fs = h ? bf_hi(a) : bf_lo(a), fd = h ? bf_hi(b) : bf_lo(b);
                    const uint32_t ua = wa[(2 * k + h) * 32], ub = wb[(2 * k + h) * 32], uv = wv[(2 * k + h) * 32];
                    g0 += fd * bf_lo(ua) + fs * bf_lo(ub);
                    g1 += fd * bf_hi(ua) + fs * bf_hi(ub);
                    v0 += fs * bf_lo(uv);
                    v1 += fs * bf_hi(uv);
                }
            }
            const float ev = __bfloat162float(p.e[i0 + l]);
            const float e0 = rcp(1.f + __expf(-(g0 + ev * bf_lo(wc))));
            const float e1 = rcp(1.f + __expf(-(g1 + ev * bf_hi(wc))));
            float* a = acc + d * 128 + 2 * lane;
            atomicAdd(a, e0);
            atomicAdd(a + 1, e1);
            atomicAdd(a + 64, e0 * v0);
            atomicAdd(a + 65, e1 * v1);
        }
    }
    bar_sync<B_EDGE, NT>();
    for (int n = warp; n < nvalid; n += NW) {
        const uint32_t xd = x2[(node0 + n) * 32 + lane];
        float u0 = 0.f, u1 = 0.f;
#pragma unroll 4
        for (int k = 0; k < 32; k++) {
            const uint32_t b = __shfl_sync(0xffffffffu, xd, k);
            const uint32_t w0 = wu[(2 * k) * 32], w1 = wu[(2 * k + 1) * 32];
            u0 += bf_lo(b) * bf_lo(w0) + bf_hi(b) * bf_lo(w1);
            u1 += bf_lo(b) * bf_hi(w0) + bf_hi(b) * bf_hi(w1);
        }
        const float* a = acc + n * 128 + 2 * lane;
        const float z0 = u0 + a[64] * rcp(a[0] + 1e-6f), z1 = u1 + a[65] * rcp(a[1] + 1e-6f);
        const float r0 = z0 > 0.f ? z0 : 0.f * z0, r1 = z1 > 0.f ? z1 : 0.f * z1;
        reinterpret_cast<uint32_t*>(p.out)[(node0 + n) * 32 + lane] = pack_bf16(bf_lo(xd) + r0, bf_hi(xd) + r1);
    }
}

__device__ __noinline__ void redo_small(const void* px, const void* pwb, const void* pwv, const void* pwc, void* pout,
                                        uint32_t flags, int wg, int node0) {
    extern __shared__ __align__(1024) unsigned char sm[];
    const int lane = threadIdx.x & 31, g = lane >> 2, t = lane & 3;
    uint32_t i0 = 0;
    float den = 0.f, num = 0.f;
#pragma unroll 1
    for (uint32_t m; (m = __ballot_sync(0xffffffffu, flags != 0)) != 0;) {
        const int l = __ffs(m) - 1;
        const uint32_t k = __ffs(__shfl_sync(0xffffffffu, flags, l)) - 1;
        const uint32_t pr = ((threadIdx.x >> 5) & 3) * 8 + (l >> 2);
        const uint32_t ta = reinterpret_cast<const uint2*>(sm + SM_GI)[(wg * GPW + (k & 15) - (16 - GPW)) * 8 + 2 * (l & 3) + (k >> 4)].x;
        const uint32_t n = (ta - SB - SM_TBL) >> 8;
        const uint32_t deg = reinterpret_cast<const uint32_t*>(sm + SM_DEG)[n];
        const uint32_t base = (reinterpret_cast<const uint32_t*>(sm + SM_CUR)[n] >> 2) - 8 * deg;
        const uint2 tb = lds64(ta ^ (pr * 8));
        uint4 xr[4][2];
        uint32_t en[4], wr[16];
#pragma unroll
        for (int u = 0; u < 4; u++) {
            en[u] = reinterpret_cast<const uint32_t*>(sm + SM_ENT)[base + 8 * min(i0 + 8 * u + g, max(deg, 1u) - 1)];
            xr[u][0] = __ldg(reinterpret_cast<const uint4*>(px) + (en[u] & 0xffff) * 8 + 2 * t);
            xr[u][1] = __ldg(reinterpret_cast<const uint4*>(px) + (en[u] & 0xffff) * 8 + 2 * t + 1);
        }
        const uint16_t* w = reinterpret_cast<const uint16_t*>((g & 1) ? pwv : pwb) + 16 * t * 64 + 2 * pr + ((g >> 1) & 1);
#pragma unroll
        for (int i = 0; i < 16; i++) wr[i] = __ldg(w + i * 64);
        uint32_t x;
        asm volatile("ld.volatile.global.u32 %0, [%1];" : "=r"(x) : "l"(reinterpret_cast<const uint32_t*>(px) + (node0 + n) * 32 + pr));
        const float wc = bf_lo(__ldg(reinterpret_cast<const uint16_t*>(pwc) + 2 * pr + (t & 1)));
        const float a = 2.f * ((t & 1) ? h_hi(tb.x) : h_lo(tb.x));
#pragma unroll
        for (int u = 0; u < 4; u += 2) {
            float c[4] = {0.f, 0.f, 0.f, 0.f};
#pragma unroll
            for (int q = 0; q < 4; q++) {
                const uint4 r0 = xr[u][q >> 1], r1 = xr[u + 1][q >> 1];
                asm("mma.sync.aligned.m16n8k16.row.col.f32.bf16.bf16.f32 {%0,%1,%2,%3}, {%4,%5,%6,%7}, {%8,%9}, {%0,%1,%2,%3};"
                    : "+f"(c[0]), "+f"(c[1]), "+f"(c[2]), "+f"(c[3])
                    : "r"((q & 1) ? r0.z : r0.x), "r"((q & 1) ? r1.z : r1.x), "r"((q & 1) ? r0.w : r0.y), "r"((q & 1) ? r1.w : r1.y),
                      "r"(wr[4 * q] | wr[4 * q + 1] << 16), "r"(wr[4 * q + 2] | wr[4 * q + 3] << 16));
            }
#pragma unroll
            for (int h = 0; h < 2; h++) {
                float eta = rcp(1.f + __expf(-(a + c[2 * h] + h_hi(en[u + h]) * wc)));
                eta = i0 + 8 * (u + h) + g < deg ? eta : 0.f;
                den += eta;
                num += eta * c[2 * h + 1];
            }
        }
        i0 += 32;
        if (i0 >= deg) {
#pragma unroll
            for (int o = 4; o < 32; o <<= 1) { den += __shfl_xor_sync(0xffffffffu, den, o); num += __shfl_xor_sync(0xffffffffu, num, o); }
            const float agg = 256.f * num * rcp(den + 1e-6f);
            const uint32_t o = finish2(__shfl_sync(0xffffffffu, agg, 0) + h_lo(tb.y), __shfl_sync(0xffffffffu, agg, 1) + h_hi(tb.y), x);
            if (lane == l) {
                if (!(ta & 8)) reinterpret_cast<uint32_t*>(pout)[(node0 + n) * 32 + pr] = o;
                flags &= flags - 1;
            }
            i0 = 0; den = 0.f; num = 0.f;
        }
    }
}

template <int MODE>
__global__ void __launch_bounds__(NTA, 1) gatedgcn_kernel(const __grid_constant__ Params p, const __grid_constant__ CUtensorMap xmap,
                                                          const __grid_constant__ CUtensorMap hmap) {
    extern __shared__ __align__(1024) unsigned char sm[];
    constexpr uint32_t sb = SB;
    spin_limit((uint32_t)__cvta_generic_to_shared(sm) != SB ? ~0u : 0u);
    const int tid = threadIdx.x, lane = tid & 31;
    const int warp = __shfl_sync(0xffffffffu, tid >> 5, 0);
    const int wg = warp >> 2, w4 = warp & 3, g8 = lane >> 2, t4 = lane & 3, tw = tid & 127;
    const int cta = blockIdx.x;
    const int node0 = cta * p.npc;
    const int nvalid = min(p.npc, p.N - node0);
    const int ch = 16 * w4 + 2 * g8;
    const uint64_t xa = reinterpret_cast<uint64_t>(p.x) + (uint64_t)node0 * 128, oa = reinterpret_cast<uint64_t>(p.out) + (uint64_t)node0 * 128;
    const uint32_t xrow0 = (uint32_t)xa;

    const uint32_t share = cta == 0 ? 1024 - G + 1 : 1;

    uint32_t* s_hist = reinterpret_cast<uint32_t*>(sm + SM_HIST);
    uint32_t* s_deg = reinterpret_cast<uint32_t*>(sm + SM_DEG);
    uint32_t* s_cur = reinterpret_cast<uint32_t*>(sm + SM_CUR);
    uint2* s_gi = reinterpret_cast<uint2*>(sm + SM_GI);
    uint32_t* s_dh = reinterpret_cast<uint32_t*>(sm + SM_DH);
    uint32_t* s_lg = reinterpret_cast<uint32_t*>(sm + SM_LG);
    uint32_t* s_end = reinterpret_cast<uint32_t*>(sm + SM_END);
    uint32_t* s_misc = reinterpret_cast<uint32_t*>(sm + SM_MISC);
    uint32_t* s_ent = reinterpret_cast<uint32_t*>(sm + SM_ENT);
    auto max_tiles = [&]() {
        uint32_t tm = 0;
#pragma unroll
        for (int k = 0; k < NWG; k++) tm = max(tm, (s_misc[M_STEP0 + 1 + k] - s_misc[M_STEP0 + k] + NSTEP - 1) / NSTEP);
        return tm;
    };

    PROF(0);
    if (wg == NWG) {
        if (tw == 0) {
#pragma unroll
            for (int i = 0; i < 4; i++) mbar_init(sb + SM_LBAR + 8 * i);
            proxy_fence();
            if (MODE & 2) {
                expect_tx(sb + SM_LBAR + 24, 4 * 8192 + 128);
                bulk_load(sb + SM_W, p.wa, 8192, sb + SM_LBAR + 24);
                bulk_load(sb + SM_W + 8192, p.wu, 8192, sb + SM_LBAR + 24);
                bulk_load(sb + SM_W + 16384, p.wb, 8192, sb + SM_LBAR + 24);
                bulk_load(sb + SM_W + 24576, p.wv, 8192, sb + SM_LBAR + 24);
                bulk_load(sb + SM_WC, p.wc, 128, sb + SM_LBAR + 24);
            }
        }
        asm volatile("setmaxnreg.dec.sync.aligned.u32 32;");
        uint32_t mw = 0;
        if (MODE & 2) {
            {
                const int k = (tw >> 3) & 7;
                const uint32_t one = tw >= 64 ? 0x3c00u << (16 * (k & 1)) : 0u;
                const uint4 v = make_uint4(k >> 1 == 0 ? one : 0, k >> 1 == 1 ? one : 0, k >> 1 == 2 ? one : 0, k >> 1 == 3 ? one : 0);
                reinterpret_cast<uint4*>(sm + SM_EXT)[tw] = v;
                reinterpret_cast<uint4*>(sm + SM_EXT)[tw + 128] = v;
            }
            bar_sync<1 + NWG, 128>();
            mbar_wait(sb + SM_LBAR + 24);
            if (w4 == 0) {
                mw = reinterpret_cast<uint32_t*>(sm + SM_WC)[lane];
                mw = pack_h(0.5f * bf_lo(mw), 0.5f * bf_hi(mw));
                reinterpret_cast<uint32_t*>(sm + SM_WC)[lane] = mw;
                mw = hmag(mw);
            }
#pragma unroll 1
            for (int j = 0; j < 8; j++) {
                const uint4* w = reinterpret_cast<const uint4*>(sm + SM_W + j * 4096) + tw * 2;
                const uint4 a = w[0], b = w[1];
                __syncwarp();
                const uint32_t m = hmag(stage_w(sm + SM_W + j * 4096, tw >> 2, (tw & 3) * 2, a, b, (j & 2) ? 256.f : 0.5f));
                mw = max((int)mw, (int)m - ((j & 2) ? 8 << 10 : 0));
            }
        }
        proxy_fence();
        bar_sync<B_SENT, NTA>();
        const uint32_t epoch = s_misc[M_EPOCH];
        if (mw > H_MAX) s_misc[M_RANGE] = 1;
        if (w4 == 0) {
            if (MODE & 2) {
                if (MODE == 3 && lane == 0) for (uint32_t it = 0; ld_relaxed(p.cnt) != epoch << 10; it++) spin_limit(it);
                __syncwarp();
                bar_arrive<B_READY, 128>();
            }
            if ((MODE & 2) && lane == 0) {
                const uint4* in = p.cell + cta * G * CV;
                proxy_fence();
                expect_tx(sb + SM_LBAR, LND);
                bulk_load(sb + SM_ENT, in, LND, sb + SM_LBAR);
                expect_tx(sb + SM_LBAR + 8, LND);
                bulk_load(sb + SM_ENT + LND, in + LND / 16, LND, sb + SM_LBAR + 8);
                expect_tx(sb + SM_LBAR + 16, G * CV * 16 - 2 * LND);
                bulk_load(sb + SM_LND2, in + LND / 8, G * CV * 16 - 2 * LND, sb + SM_LBAR + 16);
            }
            PROFT(11, NT);
            if (MODE & 1) bar_sync<B_CONV, NT + 32>();
            if (MODE == 3) mbar_wait(sb + SM_LBAR + 8);
            if (lane == 0) {
                if (MODE & 1) {
#pragma unroll 1
                    for (int b = 0; b < NWG; b++)
                        asm volatile("cp.async.bulk.tensor.2d.global.shared::cta.bulk_group [%0, {%2, %3}], [%1];"
                                     ::"l"(&hmap), "r"(sb + SM_RING + b * XROWS * 128), "r"(0), "r"(node0 + b * XROWS) : "memory");
                    asm volatile("cp.async.bulk.commit_group;" ::: "memory");
                    PROFT(12, NT);
                    if (s_misc[M_XBAD]) st_relaxed(p.cnt + 33, epoch);
                    asm volatile("cp.async.bulk.wait_group 0;" ::: "memory");
                    PROFT(13, NT);
                    asm volatile("red.release.gpu.global.add.u32 [%0], %1;" ::"l"(p.cnt + 32), "r"(share) : "memory");
                }
                if (MODE & 2) {
                    uint2 c = ld_relaxed8(p.cnt + 32);
                    for (uint32_t it = 0; c.x != epoch << 10; it++) { c = ld_relaxed8(p.cnt + 32); spin_limit(it); }
                    asm volatile("fence.acquire.gpu;" ::: "memory");
                    if (c.y == epoch) s_misc[M_LATE] = 1;
                }
                PROFT(15, NT);
            }
            __syncwarp();
        } else if (MODE & 2) {
            const uint32_t tag23 = epoch << 9;
            const int t = tw - 32;
            const int c0 = (w4 - 1) * (G / 3);
            uint32_t ln[2] = {~tag23, lane < G / 3 - 32 ? ~tag23 : tag23};
            for (uint32_t it = 0; ((ln[0] ^ tag23) | (ln[1] ^ tag23)) > 0x1ff; it++) {
#pragma unroll
                for (int r = 0; r < 2; r++)
                    if ((ln[r] ^ tag23) > 0x1ff) ln[r] = ld_relaxed(p.len + cta * LSTR + c0 + lane + 32 * r);
                spin_limit(it);
            }
            __syncwarp();
            uint32_t at[TPL] = {}, nt = 0;
#pragma unroll
            for (int r = 0; r < 2; r++) {
                const uint32_t len = ln[r] & 0x1ff;
                if (len > CAPC) s_misc[M_NOFIT] = 1;
                for (uint32_t m = __ballot_sync(0xffffffffu, len > 3 * CV && len <= CAPC); m; m &= m - 1) {
                    const uint32_t l = __ffs(m) - 1;
#pragma unroll
                    for (int k = 0; k < TPL; k++)
                        if (lane + 32 * k >= nt) at[k] = (c0 + l + 32 * r) * CX + lane + 32 * k - nt;
                    nt += __reduce_max_sync(0xffffffffu, lane == l ? len : 0) - 3 * CV;
                }
            }
            if (nt > 32 * TPL) s_misc[M_NOFIT] = 1;
            uint2 v[TPL];
#pragma unroll
            for (int k = 0; k < TPL; k++) v[k] = make_uint2(0, lane + 32 * k < nt ? ~tag23 : tag23 | 511);
            PROFT(1, NT + 32);
            bar_sync<B_READY, 128>();
            for (uint32_t it = 0; ((v[0].y ^ tag23) | (v[1].y ^ tag23) | (v[2].y ^ tag23) | (v[3].y ^ tag23)) > 0x1ff; it++) {
#pragma unroll
                for (int k = 0; k < TPL; k++)
                    if ((v[k].y ^ tag23) > 0x1ff) v[k] = ld_relaxed8(p.ext + cta * G * CX + at[k]);
                spin_limit(it);
            }
            __syncwarp();
#pragma unroll
            for (int k = 0; k < TPL; k++) atomicAdd(&s_deg[v[k].y & 0x1ff], 1u);
            PROFT(2, NT + 32);
            bar_sync<B_COUNT, NT + 96>();
            const uint32_t pv = node0 | E_PAD;
            for (int k = t; k < CAPX / 4; k += 96) reinterpret_cast<uint4*>(s_ent)[k] = make_uint4(pv, pv, pv, pv);
            bar_sync<B_SORT, NT + 96>();
            if (s_misc[M_SKIP] == 0) {
#pragma unroll
                for (int k = 0; k < TPL; k++)
                    if (lane + 32 * k < nt) s_ent[atomicAdd(&s_cur[v[k].y & 0x1ff], 32u) >> 2] = v[k].x;
            }
        }
        if (!(MODE & 2)) return;
        if (w4 != 0) bar_sync<B_GO, NT + 96>(); else bar_sync<B_ROWS, 128>();
        if (s_misc[M_SKIP] | s_misc[M_RANGE] | (s_misc[M_XBIG] ^ 1)) {
            if (w4 != 0) bar_arrive<B_ROWS, 128>(); else bar_arrive<B_CONV, NT + 32>();
            return;
        }
        const int fw = (w4 + 3) & 3;
        const uint32_t step0 = s_misc[M_STEP0 + fw];
        const int T = (s_misc[M_STEP0 + 1 + fw] - step0 + NSTEP - 1) / NSTEP;
        const int q = lane >> 3, c8 = lane & 7;
        uint32_t sidx = sb + SM_ENT + step0 * 32 + q * 8;
        uint32_t sd0 = sb + SM_RING + fw * (2 * TB) + q * 256 + ((c8 ^ (2 * q)) << 4);
        uint32_t se = sb + SM_EXT + fw * 256 + ((c8 ^ (2 * fw)) << 4) + q * 4;
        const uint32_t xlo = (uint32_t)reinterpret_cast<uint64_t>(p.x16) + c8 * 16;
        const uint32_t xhi = (uint32_t)(reinterpret_cast<uint64_t>(p.x16) >> 32);
#pragma unroll 1
        for (int i = 0; i < T; i++) {
            uint2 nx[NSTEP];
            const uint2 ee = lds64(sidx + 32 * c8);
#pragma unroll
            for (int j = 0; j < NSTEP; j++) nx[j] = lds64(sidx + 32 * j);
            const uint32_t e2 = __byte_perm(ee.x, ee.y, 0x7632);
            uint32_t pm;
            asm("set.nan.u32.f16x2 %0, %1, %1;" : "=r"(pm) : "r"(e2));
            if (i > 0) {
                cp_wait();
                proxy_fence();
                bar_sync<288>(1 + fw);
            } else if (w4 != 0) {
                bar_sync<B_ROWS, 128>();
            }
            asm volatile("st.shared.u32 [%0], %1;" ::"r"(se), "r"(e2 & ~pm) : "memory");
            asm volatile("st.shared.u32 [%0+128], %1;" ::"r"(se ^ 16), "r"(pm & 0x40004000u) : "memory");
#pragma unroll
            for (int u = 0; u < 2 * NSTEP; u++) {
                uint64_t ga;
                asm("{\n.reg .b32 lo;\ndp2a.lo.u32.u32 lo, %1, 0x80, %2;\nmov.b64 %0, {lo, %3};\n}"
                    : "=l"(ga) : "r"((u & 1) ? nx[u >> 1].y : nx[u >> 1].x), "r"(xlo), "r"(xhi));
                cp16((sd0 ^ ((u & 1) * 16)) + (u & 1) * 128 + (u >> 1) * 1024, reinterpret_cast<const void*>(ga));
            }
            cp_commit();
            sidx += NSTEP * 32;
            sd0 ^= TB;
            se ^= 2048;
        }
        cp_wait();
        proxy_fence();
        for (uint32_t i = T - 1, n = max_tiles() + (fw == 0); i < n; i++) bar_sync<288>(1 + fw);
    } else {
        const uint32_t bar = sb + SM_BAR + wg * 24;
        const int e0 = cta * p.chunk + wg * VWG * 4;
        const int nvec = min(min(p.chunk - wg * VWG * 4, p.E - e0) >> 2, VWG);
        auto load_x = [&]() {
            if (tw == 0) {
                expect_tx(bar + 16, XROWS * 128);
                asm volatile("cp.async.bulk.tensor.2d.shared::cluster.global.mbarrier::complete_tx::bytes [%0], [%1, {%3, %4}], [%2];"
                             ::"r"(sb + SM_RING + wg * XROWS * 128), "l"(&xmap), "r"(bar + 16), "r"(0), "r"(node0 + wg * XROWS) : "memory");
            }
        };
        if (tw == 0) {
#pragma unroll
            for (int i = 0; i < 3; i++) mbar_init(bar + i * 8);
            proxy_fence();
            if (MODE & 1) {
                expect_tx(bar, nvec * 16);
                bulk_load(sb + SM_RING + wg * XROWS * 128, p.dst + e0, nvec * 16, bar);
            }
        }
        if (MODE == 2) load_x();
        const uint32_t cnt0 = ld_relaxed(p.cnt + opaque32(0));

        if (tid < (SM_CUR - SM_DEG) / 16) reinterpret_cast<uint4*>(sm + SM_DEG)[tid] = make_uint4(0, 0, 0, 0);
        if (tid < 32) s_cur[NSLOT + tid] = 0x80000000u;
        if (tid < 8) s_gi[NWG * GPW * 8 + tid] = make_uint2(sb + SM_TBL, xrow0);
        if (MODE & 1) {
#pragma unroll
            for (int j = 0; j < (G * CAPC / 2 + NT - 1) / NT; j++)
                if (tid + NT * j < G * CAPC / 2) reinterpret_cast<uint4*>(sm + SM_TBL)[tid + NT * j] = make_uint4(0, 511, 0, 511);
            if (tw == 0) {
                expect_tx(bar + 8, nvec * 24);
                bulk_load(sb + SM_ENT + wg * VWG * 24, p.src + e0, nvec * 16, bar + 8);
                bulk_load(sb + SM_ENT + wg * VWG * 24 + VWG * 16, p.e + e0, nvec * 8, bar + 8);
            }
        }
        bar_sync<B_EDGE, NT>();

        const uint32_t epoch = (cnt0 >> 10) + (MODE == 2 ? 0 : 1);
        const uint32_t tag5 = epoch << 27, tag23 = epoch << 9;
        if (MODE & 1) {
            int4 dv[VPT];
            mbar_wait(bar);
#pragma unroll
            for (int j = 0; j < VPT; j++) dv[j] = reinterpret_cast<const int4*>(sm + SM_RING + wg * XROWS * 128)[tw + 128 * j];
            uint32_t key[VPT * 4];
#pragma unroll
            for (int j = 0; j < VPT; j++) {
                const bool ok = tw + 128 * j < nvec;
                const int d[4] = {dv[j].x, dv[j].y, dv[j].z, dv[j].w};
#pragma unroll
                for (int q = 0; q < 4; q++) {
                    const uint32_t b = ok ? __umulhi((uint32_t)d[q], p.magic) : G;
                    const uint32_t r = atomicAdd(&s_hist[b], 1u);
                    key[j * 4 + q] = (b * CAPC + min(r, CAPC - 1u)) | ((uint32_t)(d[q] - b * p.npc) << 16);
                }
            }
            proxy_fence();
            bar_sync<B_EDGE, NT>();
            if (tid < G) {
                st_relaxed(p.len + tid * LSTR + cta, min(s_hist[tid], 511u) | tag23);
                if (cta < (-G & 7)) p.len[tid * LSTR + G + cta] = 0;
            }
            mbar_wait(bar + 8);
            load_x();
            uint2* stage = reinterpret_cast<uint2*>(sm + SM_TBL);
            uint32_t emax = 0;
#pragma unroll
            for (int j = 0; j < VPT; j++) {
                const uint4 sv = reinterpret_cast<const uint4*>(sm + SM_ENT + wg * VWG * 24)[tw + 128 * j];
                uint2 ev = reinterpret_cast<const uint2*>(sm + SM_ENT + wg * VWG * 24 + VWG * 16)[tw + 128 * j];
                ev.x = bf2h(ev.x); ev.y = bf2h(ev.y);
                if (tw + 128 * j < nvec) emax = hamax2(emax, hamax2(ev.x, ev.y));
                const uint32_t w0[4] = {__byte_perm(sv.x, ev.x, 0x5410), __byte_perm(sv.y, ev.x, 0x7610),
                                        __byte_perm(sv.z, ev.y, 0x5410), __byte_perm(sv.w, ev.y, 0x7610)};
#pragma unroll
                for (int q = 0; q < 4; q++) stage[key[j * 4 + q] & 0xffff] = make_uint2(w0[q], key[j * 4 + q] >> 16);
            }
            if (hmag(emax) > H_MAX) {
#pragma unroll
                for (int k = 0; k < VPT * 4; k++) stage[key[k] & 0xffff].y = 510;
            }
            bar_sync<B_EDGE, NT>();
            PROF(3);
            {
                const int b = warp + NW * lane;
                const uint32_t c = b < G ? s_hist[b] : 0;
                for (uint32_t m = __ballot_sync(0xffffffffu, c > 3 * CV); m; m &= m - 1) {
                    const int l = __ffs(m) - 1, bl = warp + NW * l;
                    if (3 * CV + (lane & ~3) < __shfl_sync(0xffffffffu, c, l)) {
                        const uint2 v = stage[bl * CAPC + 3 * CV + lane];
                        st_relaxed8(p.ext + (bl * G + cta) * CX + lane, v.x, v.y | tag23);
                    }
                }
            }
            if (tid < BPR * CV) {
                const int xb = tid / CV, xi = tid - xb * CV;
                const uint2* st = stage + xb * CAPC + xi * 3;
                uint4* gc = p.cell + (xb * G + cta) * CV + xi;
                uint4 v[RND];
#pragma unroll
                for (int j = 0; j < RND; j++)
                    if (xb + BPR * j < G) {
                        const uint2 a = st[j * BPR * CAPC], b = st[j * BPR * CAPC + 1], c = st[j * BPR * CAPC + 2];
                        v[j] = make_uint4(a.x, b.x, c.x, a.y + b.y * 512 + c.y * 262144 + tag5);
                    }
#pragma unroll
                for (int j = 0; j < RND; j++)
                    if (xb + BPR * j < G) {
                        st_relaxed16(gc + j * BPR * G * CV, v[j]);
                        if (j == 2 && tid == NT - 32) asm volatile("red.relaxed.gpu.global.add.u32 [%0], %1;" ::"l"(p.cnt), "r"(share) : "memory");
                    }
            }
        }
        if (tid == 0) s_misc[M_EPOCH] = epoch;
        bar_sync<B_SENT, NTA>();
        asm volatile("setmaxnreg.inc.sync.aligned.u32 112;");
        PROF(4);
        {
            mbar_wait(bar + 16);
            uint4* xs = reinterpret_cast<uint4*>(sm + SM_RING + wg * XROWS * 128) + tw;
            uint4 v[XROWS / 16];
            uint32_t mx = 0, my = 0;
#pragma unroll
            for (int j = 0; j < XROWS / 16; j++) v[j] = xs[128 * j];
#pragma unroll
            for (int j = 0; j < XROWS / 16; j++) {
                v[j].x = bf2h(v[j].x); v[j].y = bf2h(v[j].y); v[j].z = bf2h(v[j].z); v[j].w = bf2h(v[j].w);
                xs[128 * j] = v[j];
                mx = hfma2(v[j].x, v[j].x, hfma2(v[j].z, v[j].z, mx));
                my = hfma2(v[j].y, v[j].y, hfma2(v[j].w, v[j].w, my));
            }
            if (hmag(hamax2(mx, my)) > SQ_MAX) s_misc[M_XBAD] = 1;
            if (hmag(hamax2(mx, my)) >= SQ_MIN) s_misc[M_XBIG] = 1;
            proxy_fence();
            if (MODE & 1) bar_arrive<B_CONV, NT + 32>();
            if (!(MODE & 2)) return;
            bar_sync<128>(1 + wg);
        }
        uint32_t da[24], du[24];
        {
            const uint32_t dx = (1u << 16) | ((sb + SM_RING + wg * XROWS * 128) >> 4);
            constexpr uint32_t dw = (1u << 16) | ((sb + SM_W) >> 4);
            wg_fence();
            mma_ss<0>(da, dw, dx);
            mma_ss<0>(du, dw + 512, dx);
#pragma unroll
            for (int k = 1; k < 4; k++) { mma_ss<1>(da, dw + 128 * k, dx + 2 * k); mma_ss<1>(du, dw + 512 + 128 * k, dx + 2 * k); }
            wg_commit();
            wg_wait();
            keep(da); keep(du);
        }
        auto table = [&]() {
            unsigned char* tb = sm + SM_TBL + (wg * XROWS + 2 * t4) * 256 + ((ch * 4) ^ (t4 << 5));
            uint32_t am = 0;
#pragma unroll
            for (int j = 0; j < 12; j++) {
                am = hamax2(am, hamax2(da[2 * j], da[2 * j + 1]));
#pragma unroll
                for (int h = 0; h < 2; h++)
                    if (j < 11 || wg * XROWS + 8 * j + 2 * t4 + h < NROW)
                        *reinterpret_cast<uint2*>(tb + (8 * j + h) * 256) =
                            make_uint2(__byte_perm(da[2 * j], da[2 * j + 1], h ? 0x7632 : 0x5410), __byte_perm(du[2 * j], du[2 * j + 1], h ? 0x7632 : 0x5410));
            }
            if (hmag(am) > A_MAX) s_misc[M_RANGE] = 1;
        };
        if (wg < NWG - 1) table();
        PROF(5);
        uint4 en[RNC];
        uint32_t d4[RNC * 3];
        auto count = [&](int j0, int j1) {
            mbar_wait(sb + SM_LBAR + 4 * j0);
#pragma unroll
            for (int j = j0; j < j1; j++) {
                if (j < RNC - 1 || tid + j * NT < G * CV) en[j] = reinterpret_cast<const uint4*>(sm + (j < 4 ? SM_ENT : SM_LND2 - 2 * LND))[j * NT + tid];
                else en[j] = make_uint4(0, 0, 0, tag5 | 0x7ffffffu);
            }
            for (uint32_t it = 0;; it++) {
                uint32_t miss = 0;
#pragma unroll
                for (int j = j0; j < j1; j++) miss |= en[j].w ^ tag5;
                if (miss < (1u << 27)) break;
#pragma unroll
                for (int j = j0; j < j1; j++)
                    ld_relaxed16_if(en[j], p.cell + cta * G * CV + tid + j * NT, (en[j].w ^ tag5) >= (1u << 27));
                spin_limit(it);
            }
            __syncwarp();
#pragma unroll
            for (int j = j0; j < j1; j++)
#pragma unroll
                for (int s = 0; s < 3; s++) {
                    d4[3 * j + s] = (s == 0 ? en[j].w << 2 : en[j].w >> (9 * s - 2)) & 0x7fc;
                    asm volatile("red.shared.add.u32 [%0+%1], 1;" ::"r"(d4[3 * j + s]), "n"(sb + SM_DEG) : "memory");
                }
        };
        count(0, 2);
        count(2, 4);
        PROF(6);
        count(4, RNC);
        bar_sync<B_COUNT, NT + 96>();
        PROF(7);
        uint32_t unused = 0;
        if (warp < NSLOT / 32) {
            const uint32_t dg = s_deg[tid];
            if (dg > 62 || s_deg[510] || xrow0 > ~0u - NSLOT * 128 || (uint32_t)oa > ~0u - NSLOT * 128) s_misc[M_NOFIT] = 1;
            const uint32_t kb = tid < nvalid ? 62 - min(dg, 62u) : 63;
            const uint32_t r = atomicAdd(&s_dh[kb], 1u);
            bar_sync<B_NODE, NSLOT>();
            const uint2 h = reinterpret_cast<const uint2*>(s_dh)[lane];
            uint32_t inc = h.x + h.y;
#pragma unroll
            for (int o = 1; o < 32; o <<= 1) { const uint32_t v = __shfl_up_sync(0xffffffffu, inc, o); if (lane >= o) inc += v; }
            const uint32_t pe = __shfl_sync(0xffffffffu, inc - h.x - h.y, kb >> 1), po = __shfl_sync(0xffffffffu, inc - h.y, kb >> 1);
            const uint32_t pos = ((kb & 1) ? po : pe) + r;
            const uint32_t grp = pos >> 3, slot = pos & 7, row = grp / NWG, col = grp - row * NWG;
            const uint32_t seg = (row & 1) ? NWG - 1 - col : col;
            const uint32_t idx = seg * GPW + GPW - 1 - row;
            if (slot == 0) s_lg[idx] = max(dg, (uint32_t)NSTEP);
            bar_sync<B_NODE, NSLOT>();
            const uint2 l = reinterpret_cast<const uint2*>(s_lg)[lane];
            uint32_t in2 = l.x + l.y;
#pragma unroll
            for (int o = 1; o < 32; o <<= 1) { const uint32_t v = __shfl_up_sync(0xffffffffu, in2, o); if (lane >= o) in2 += v; }
            const uint32_t ex2 = in2 - l.x - l.y;
            const uint32_t mine = __shfl_sync(0xffffffffu, ex2, (lane / (GPW / 2)) * (GPW / 2));
            const uint32_t ee = __shfl_sync(0xffffffffu, in2 - l.y, idx >> 1), eo = __shfl_sync(0xffffffffu, in2, idx >> 1);
            const uint32_t sbeg = __shfl_sync(0xffffffffu, ex2, seg * (GPW / 2));
            if (__any_sync(0xffffffffu, in2 > CAP / 8 || in2 - mine > MAXT * NSTEP) || s_misc[M_NOFIT] != 0) {
                s_misc[M_SKIP] = 1;
            } else {
                const uint32_t gend = (idx & 1) ? eo : ee;
                s_cur[tid] = (gend - dg) * 32 + slot * 4;
                if (tid < nvalid) s_gi[idx * 8 + slot] = make_uint2(sb + SM_TBL + tid * 256 + (((tid >> 1) & 3) << 5), xrow0 + tid * 128);
                else unused = (idx * 8 + slot) | ((seg * GPW + GPW - 1) * 8 + slot) << 16;
                if (slot == 0) {
                    const uint32_t last = gend - 1 - sbeg;
                    s_end[seg * MAXT + last / NSTEP] = last % NSTEP + 1;
                }
                if (tid <= NWG * (GPW / 2) && tid % (GPW / 2) == 0) s_misc[M_STEP0 + tid / (GPW / 2)] = ex2;
            }
        } else {
            table();
        }
        bar_sync<B_SORT, NT + 96>();
        PROF(8);
        if (s_misc[M_SKIP] == 0) {
            if (unused) { const uint2 v = s_gi[unused >> 16]; s_gi[unused & 0xffff] = make_uint2(v.x ^ 8, v.y); }
            auto place = [&](int j1) {
#pragma unroll
                for (int k = 0; k < 3 * j1; k++)
                    asm volatile("atom.shared.add.u32 %0, [%1+%2], 32;" : "=r"(d4[k]) : "r"(min(d4[k], (NSLOT + lane) * 4u)), "n"(sb + SM_CUR) : "memory");
#pragma unroll
                for (int j = 0; j < j1; j++)
#pragma unroll
                    for (int s = 0; s < 3; s++)
                        asm volatile("{\n.reg .pred q;\nsetp.ge.s32 q, %0, 0;\n@q st.shared.u32 [%0+%2], %1;\n}"
                                     ::"r"(d4[3 * j + s]), "r"(s == 0 ? en[j].x : s == 1 ? en[j].y : en[j].z), "n"(sb + SM_ENT));
            };
            if (warp * 32 + (RNC - 1) * NT < G * CV) place(RNC); else place(RNC - 1);
        }
        bar_sync<B_GO, NT + 96>();
        PROF(9);
        uint32_t plain = s_misc[M_SKIP] | s_misc[M_RANGE] | (s_misc[M_XBIG] ^ 1);
        if (plain) {
            bar_sync<B_CONV, NT + 32>();
        } else {
            __nanosleep(wg * 120);
            uint32_t fb[16], fv[16], fe[4];
            {
                const uint32_t a = sb + SM_W + 16384 + ((lane >> 4) * 8 + (lane & 7)) * 128 + (((2 * w4 + ((lane >> 3) & 1)) ^ (lane & 7)) << 4);
#pragma unroll
                for (int k = 0; k < 4; k++) {
                    ldsm_t(fb + 4 * k, a + k * 2048);
                    ldsm_t(fv + 4 * k, a + 8192 + k * 2048);
                }
                const uint32_t wh = reinterpret_cast<const uint32_t*>(sm + SM_WC)[ch >> 1];
                fe[0] = t4 != wg ? 0 : __byte_perm(wh, 0xfb53, 0x5410);
                fe[1] = t4 != wg ? 0 : __byte_perm(wh, 0xfb53, 0x5432);
                fe[2] = fe[3] = 0;
            }
            const uint32_t step0 = __shfl_sync(0xffffffffu, s_misc[M_STEP0 + wg], 0);
            const uint32_t T = (__shfl_sync(0xffffffffu, s_misc[M_STEP0 + 1 + wg], 0) - step0 + NSTEP - 1) / NSTEP;
            uint32_t dx = (1u << 16) | ((sb + SM_RING + wg * (2 * TB)) >> 4);
            uint32_t de = (1u << 16) | ((sb + SM_EXT) >> 4);
            uint32_t ma = sb + SM_END + wg * MAXT * 4;
            uint32_t gptr = opaque32(sb + SM_GI + wg * GPW * 64 + t4 * 16);
            auto pin = [&](uint32_t v) { return __shfl_sync(0xffffffffu, v + lane, lane) - lane; };
            const uint32_t tb4 = pin(ch * 4), chx = pin(ch * 2), cho = pin(ch * 2 + (uint32_t)oa - xrow0);
            uint64_t px[2], po[2];
#pragma unroll
            for (int h = 0; h < 2; h++) {
                px[h] = (uint64_t)(pin((uint32_t)(xa >> 32) + h) - h) << 32;
                po[h] = (uint64_t)(pin((uint32_t)(oa >> 32) + h) - h) << 32;
            }
            const uint32_t turn = pin(1 + wg), next = pin(1 + ((wg + 1) & 3));
            uint32_t flags = 0;
#pragma unroll 1
            for (int row = GPW - 1; (row + 1) * NWG * 8 > nvalid; row--) {
                const int pos = (row * NWG + ((row & 1) ? NWG - 1 - wg : wg)) * 8 + 2 * t4;
                flags |= ((pos + 1 >= nvalid ? 1u : 0u) | (pos >= nvalid ? 0x10000u : 0u)) << (GPW - 1 - row);
            }
            auto set_lo = [&](uint64_t& a, uint32_t r, uint32_t c) {
                asm("{\n.reg .b32 lo, hi;\nmov.b64 {lo, hi}, %0;\nadd.u32 lo, %1, %2;\nmov.b64 %0, {lo, hi};\n}" : "+l"(a) : "r"(r), "r"(c));
            };
            uint32_t hN[2], hD[2], hA[2], u2[2], x2[2] = {0, 0}, zmax = 0;
            uint4 gi;
            uint2 t0, t1;
            auto fetch_group = [&]() {
                gi = lds128(gptr);
                gptr += 64;
                t0 = lds64(gi.x ^ tb4); t1 = lds64(gi.z ^ tb4);
            };
            auto next_a = [&]() {
                const uint32_t a0 = __byte_perm(t0.x, t1.x, 0x5410), a1 = __byte_perm(t0.x, t1.x, 0x7632);
                hA[0] = hsub2(a0, fe[2]); hA[1] = hsub2(a1, fe[3]);
                fe[2] = a0; fe[3] = a1;
            };
            auto next_rows = [&]() {
                set_lo(px[0], gi.y, chx); set_lo(px[1], gi.w, chx);
                set_lo(po[0], gi.y, cho); set_lo(po[1], gi.w, cho);
                u2[0] = __byte_perm(t0.y, t1.y, 0x5410); u2[1] = __byte_perm(t0.y, t1.y, 0x7632);
            };
            auto flush_group = [&](const uint32_t (&hN)[2], const uint32_t (&hD)[2]) {
                uint32_t z[2];
#pragma unroll
                for (int r = 0; r < 2; r++) {
                    const float d0 = h_lo(hD[r]), d1 = h_hi(hD[r]);
                    const float rr = rcp(d0 * d1);
                    uint32_t r2;
                    asm("cvt.rn.satfinite.f16x2.f32 %0, %1, %2;" : "=r"(r2) : "f"(rr * d0), "f"(rr * d1));
                    z[r] = hfma2(hN[r], r2, u2[r]);
                }
                const uint32_t o0 = finish2(h_lo(z[0]), h_lo(z[1]), x2[0]), o1 = finish2(h_hi(z[0]), h_hi(z[1]), x2[1]);
                asm volatile("st.global.u32 [%0], %1;" ::"l"(po[0]), "r"(o0) : "memory");
                asm volatile("st.global.u32 [%0], %1;" ::"l"(po[1]), "r"(o1) : "memory");
                zmax = hamax2(zmax, hamax2(z[0], z[1]));
                flags = __funnelshift_r(flags, flags, 1) ^ (~(__vminu2(hD[0], hD[1]) + (0x80008000u - DEN_SMALL)) & 0x80008000u);
            };
            auto gate = [&](uint32_t g) { return pack_h(1.f + tanh_(h_lo(g)), 1.f + tanh_(h_hi(g))); };
            uint32_t db[2 * NSTEP], dv[2 * NSTEP];
            fetch_group();
            next_a();
            next_rows();
            hN[0] = hN[1] = 0; hD[0] = hD[1] = DEN0;
            if (wg == NWG - 1) bar_arrive<1, 288>();
            const uint32_t mend = ma + 4 * T;
#pragma unroll 1
            while (ma != mend) {
                uint32_t m;
                asm volatile("ld.shared.u32 %0, [%1];" : "=r"(m) : "r"(ma));
                ma += 4;
                bar_sync<288>(turn);
                wg_fence();
                mma_rs<0, 0>(dv, fv, dx);
                mma_rs<0, 0>(db, fb, dx);
#pragma unroll
                for (int k = 1; k < 4; k++) {
                    mma_rs<1, 0>(dv, fv + 4 * k, dx + 2 * k);
                    mma_rs<1, 0>(db, fb + 4 * k, dx + 2 * k);
                }
                mma_rs<1, 1>(db, fe, de);
                wg_commit();
                dx ^= TB >> 4;
                de ^= 128;
                auto block = [&](int e) {
                    bar_arrive<288>(next);
                    if (e > 0) {
                        asm volatile("ld.global.nc.u32 %0, [%1];" : "=r"(x2[0]) : "l"(px[0]));
                        asm volatile("ld.global.nc.u32 %0, [%1];" : "=r"(x2[1]) : "l"(px[1]));
                        fetch_group();
                    }
                    wg_wait();
                    keep(dv); keep(db); keep(fe);
                    if (e > 0) next_a();
                    uint32_t oN[2], oD[2];
#pragma unroll
                    for (int j = 0; j < NSTEP; j++) {
#pragma unroll
                        for (int r = 0; r < 2; r++) {
                            const uint32_t w = gate(e > 0 && j >= e ? hadd2(db[2 * j + r], hA[r]) : db[2 * j + r]);
                            hN[r] = hfma2(w, dv[2 * j + r], hN[r]);
                            hD[r] = hadd2(w, hD[r]);
                        }
                        if (j + 1 == e) {
                            oN[0] = hN[0]; oN[1] = hN[1]; oD[0] = hD[0]; oD[1] = hD[1];
                            hN[0] = hN[1] = 0; hD[0] = hD[1] = DEN0;
                        }
                    }
                    if (e > 0) { flush_group(oN, oD); next_rows(); }
                };
                if (m == 0) block(0);
                else if (m > 4) { if (m > 6) { if (m > 7) block(8); else block(7); } else { if (m > 5) block(6); else block(5); } }
                else { if (m > 2) { if (m > 3) block(4); else block(3); } else { if (m > 1) block(2); else block(1); } }
            }
            PROF(10);
            for (uint32_t i = T, n = max_tiles(); i < n; i++) {
                bar_sync<288>(turn);
                bar_arrive<288>(next);
            }
            if (wg == 0) bar_sync<1, 288>();
            if (__any_sync(0xffffffffu, flags != 0)) redo_small(p.x, p.wb, p.wv, p.wc, p.out, flags, wg, node0);
            asm volatile("{\n.reg .pred q;\nsetp.ge.u32 q, %1, 0x7c00;\nbar.red.or.pred q, %2, %3, q;\nselp.u32 %0, 1, 0, q;\n}"
                         : "=r"(plain) : "r"(hmag(zmax) | s_misc[M_LATE] << 15), "n"((int)B_FINAL), "n"(NT) : "memory");
        }
        if (plain) slow_bin(p, sm, node0, nvalid);
        PROF(14);
    }
}

typedef CUresult (*EncodeFn)(CUtensorMap*, CUtensorMapDataType, cuuint32_t, void*, const cuuint64_t*, const cuuint64_t*,
                             const cuuint32_t*, const cuuint32_t*, CUtensorMapInterleave, CUtensorMapSwizzle,
                             CUtensorMapL2promotion, CUtensorMapFloatOOBfill);

}

extern "C" void kernel_launch(void* const* d_in, const int* in_sizes, int n_in, void* d_out, int out_size) {
    static int sms = 0;
    static EncodeFn encode = nullptr;
    static void *cell = nullptr, *ext = nullptr, *cnt = nullptr, *x16 = nullptr, *len = nullptr;
    if (!sms) {
        int dev = 0;
        cudaGetDevice(&dev);
        cudaDeviceGetAttribute(&sms, cudaDevAttrMultiProcessorCount, dev);
        cudaFuncSetAttribute(gatedgcn_kernel<1>, cudaFuncAttributeMaxDynamicSharedMemorySize, SM_TOTAL);
        cudaFuncSetAttribute(gatedgcn_kernel<2>, cudaFuncAttributeMaxDynamicSharedMemorySize, SM_TOTAL);
        cudaFuncSetAttribute(gatedgcn_kernel<3>, cudaFuncAttributeMaxDynamicSharedMemorySize, SM_TOTAL);
        cudaDriverEntryPointQueryResult qr;
        cudaGetDriverEntryPoint("cuTensorMapEncodeTiled", (void**)&encode, cudaEnableDefault, &qr);
        cudaGetSymbolAddress(&cell, g_cell);
        cudaGetSymbolAddress(&ext, g_ext);
        cudaGetSymbolAddress(&cnt, g_cnt);
        cudaGetSymbolAddress(&len, g_len);
        cudaGetSymbolAddress(&x16, g_x16);
        if (((uint64_t)x16 >> 32) != (((uint64_t)x16 + G * NSLOT * 128 - 1) >> 32)) x16 = (char*)x16 + G * NSLOT * 128;
    }
    Params p;
    p.x = (const __nv_bfloat16*)d_in[0];
    p.e = (const __nv_bfloat16*)d_in[1];
    p.src = (const int*)d_in[2];
    p.dst = (const int*)d_in[3];
    p.wa = (const __nv_bfloat16*)d_in[4];
    p.wb = (const __nv_bfloat16*)d_in[5];
    p.wc = (const __nv_bfloat16*)d_in[6];
    p.wu = (const __nv_bfloat16*)d_in[7];
    p.wv = (const __nv_bfloat16*)d_in[8];
    p.out = (__nv_bfloat16*)d_out;
    p.cell = (uint4*)cell;
    p.ext = (uint64_t*)ext;
    p.len = (uint32_t*)len;
    p.cnt = (uint32_t*)cnt;
    p.x16 = (const uint4*)x16;
    p.N = in_sizes[0] / 64;
    p.E = in_sizes[2];
    p.npc = (p.N + G - 1) / G;
    p.chunk = ((p.E + G - 1) / G + 7) & ~7;
    p.magic = (uint32_t)(0x100000000ull / (uint32_t)p.npc) + 1u;
    if (!encode || p.npc > NROW || p.N - (G - 1) * p.npc < 8 * NWG || p.chunk > CHUNK_MAX || (p.E & 7) ||
        p.E - (G - 1) * p.chunk <= (NWG - 1) * VWG * 4) return;

    CUtensorMap xmap, hmap;
    const cuuint64_t dims[2] = {64, (cuuint64_t)p.N};
    const cuuint64_t strides[1] = {128};
    const cuuint32_t box[2] = {64, XROWS}, estr[2] = {1, 1};
    encode(&xmap, CU_TENSOR_MAP_DATA_TYPE_BFLOAT16, 2, d_in[0], dims, strides, box, estr, CU_TENSOR_MAP_INTERLEAVE_NONE,
           CU_TENSOR_MAP_SWIZZLE_128B, CU_TENSOR_MAP_L2_PROMOTION_L2_256B, CU_TENSOR_MAP_FLOAT_OOB_FILL_NONE);
    encode(&hmap, CU_TENSOR_MAP_DATA_TYPE_FLOAT16, 2, x16, dims, strides, box, estr, CU_TENSOR_MAP_INTERLEAVE_NONE,
           CU_TENSOR_MAP_SWIZZLE_128B, CU_TENSOR_MAP_L2_PROMOTION_NONE, CU_TENSOR_MAP_FLOAT_OOB_FILL_NONE);
    if (sms >= G) {
        gatedgcn_kernel<3><<<G, NTA, SM_TOTAL>>>(p, xmap, hmap);
    } else {
        gatedgcn_kernel<1><<<G, NTA, SM_TOTAL>>>(p, xmap, hmap);
        gatedgcn_kernel<2><<<G, NTA, SM_TOTAL>>>(p, xmap, hmap);
    }
}
```

```cpp
#include <cuda_runtime.h>
#include <cuda_bf16.h>
#include <cuda_fp16.h>
#include <cuda.h>
#include <stdint.h>

namespace {

constexpr int G = 132;
constexpr int NWG = 4;
constexpr int NT = NWG * 128;
constexpr int NW = NT / 32;
constexpr int NTA = NT + 128;
constexpr int NSLOT = 384;
constexpr int NROW = 380;
constexpr int GPW = NSLOT / 8 / NWG;
constexpr int XROWS = NSLOT / NWG;
constexpr int VPT = 3;
constexpr int VWG = 128 * VPT;
constexpr int CHUNK_MAX = NT * VPT * 4;
constexpr int CV = 18;
constexpr int CX = 32;
constexpr int CAPC = 3 * CV + CX;
constexpr int LSTR = 160;
constexpr int BPR = NT / CV;
constexpr int RND = (G + BPR - 1) / BPR;
constexpr int RNC = (G * CV + NT - 1) / NT;
constexpr int TPL = 4;
constexpr int NSTEP = 8;
constexpr int TB = NSTEP * 8 * 128;
constexpr int CAP = 6784;
constexpr int CAPX = CAP + NSTEP * 8;
constexpr int MAXT = 40;
static_assert(GPW % 2 == 0 && GPW <= 16 && G % 3 == 0 && G <= 192 && RNC == 5, "layout");

constexpr uint32_t SB = 1024;
constexpr int SM_RING = 0;
constexpr int SM_W = SM_RING + NSLOT * 128;
constexpr int SM_TBL = SM_W + 4 * 8192;
constexpr int SM_ENT = SM_TBL + NROW * 256;
constexpr int SM_EXT = SM_ENT + CHUNK_MAX * 6;
constexpr int SM_DEG = SM_EXT + 4096;
constexpr int SM_DH = SM_DEG + 512 * 4;
constexpr int SM_LG = SM_DH + 64 * 4;
constexpr int SM_END = SM_LG + 64 * 4;
constexpr int SM_MISC = SM_END + NWG * MAXT * 4;
constexpr int SM_HIST = SM_MISC + 64;
constexpr int SM_CUR = SM_HIST + 144 * 4;
constexpr int SM_GI = SM_CUR + 512 * 4;
constexpr int SM_BAR = SM_GI + (NWG * GPW + 1) * 64;
constexpr int SM_LBAR = SM_BAR + 96;
constexpr int SM_WC = SM_LBAR + 32;
constexpr int SM_TOTAL = SM_WC + 128;
constexpr int LND = 2 * NT * 16;
constexpr int SM_LND2 = SM_TBL + (NWG - 1) * XROWS * 256;
static_assert(SM_TOTAL <= 232448 && NSLOT * 128 * 4 <= SM_DEG, "smem");
static_assert(NWG * 2 * TB <= SM_W + 16384 && SM_TBL % 1024 == 0 && SM_EXT % 1024 == 0 && (SB + SM_EXT) % 4096 < 2048, "align");
static_assert((G + 1) * CAPC * 8 <= NROW * 256 && CAPC % 2 == 0, "outgoing cells");
static_assert(CAPX * 4 <= CHUNK_MAX * 6 && 2 * LND <= CHUNK_MAX * 6 && SM_LND2 + G * CV * 16 - 2 * LND <= SM_ENT, "aliases");
static_assert(SM_CUR % 16 == 0 && SM_GI % 16 == 0 && SM_WC % 16 == 0, "vector access");
enum { M_NOFIT, M_LATE, M_XBIG, M_XBAD, M_RANGE, M_SKIP, M_EPOCH, M_STEP0 = 8 };
enum { B_EDGE = 6, B_NODE, B_SENT, B_FINAL, B_CONV, B_COUNT, B_READY, B_SORT, B_GO, B_ROWS };

__device__ __align__(128) uint4 g_cell[G * G * CV];
__device__ __align__(128) uint64_t g_ext[G * G * CX];
__device__ __align__(128) uint32_t g_len[G * LSTR];
__device__ __align__(128) uint4 g_x16[2 * G * NSLOT * 8];
__device__ __align__(128) uint32_t g_cnt[64];

constexpr uint32_t DEN0 = 0x00220022u;
constexpr uint32_t DEN_SMALL = 0x03470347u;
constexpr uint32_t E_PAD = 0xffff0000u;
constexpr uint32_t H_MAX = 0x4ff0u;
constexpr uint32_t A_MAX = 0x5000u;
constexpr uint32_t SQ_MAX = 0x6380u;
constexpr uint32_t SQ_MIN = 0x2240u;

__device__ __forceinline__ float tanh_(float x) { float y; asm("tanh.approx.f32 %0, %1;" : "=f"(y) : "f"(x)); return y; }
__device__ __forceinline__ float rcp(float x) { float y; asm("rcp.approx.ftz.f32 %0, %1;" : "=f"(y) : "f"(x)); return y; }
__device__ __forceinline__ uint32_t pack_bf16(float lo, float hi) { uint32_t r; asm("cvt.rn.bf16x2.f32 %0, %1, %2;" : "=r"(r) : "f"(hi), "f"(lo)); return r; }
__device__ __forceinline__ uint32_t pack_h(float lo, float hi) { uint32_t r; asm("cvt.rn.f16x2.f32 %0, %1, %2;" : "=r"(r) : "f"(hi), "f"(lo)); return r; }
__device__ __forceinline__ float h_lo(uint32_t v) { return __low2float(*reinterpret_cast<__half2*>(&v)); }
__device__ __forceinline__ float h_hi(uint32_t v) { return __high2float(*reinterpret_cast<__half2*>(&v)); }
__device__ __forceinline__ uint32_t hadd2(uint32_t a, uint32_t b) { uint32_t r; asm("add.rn.f16x2 %0, %1, %2;" : "=r"(r) : "r"(a), "r"(b)); return r; }
__device__ __forceinline__ uint32_t hsub2(uint32_t a, uint32_t b) { uint32_t r; asm("sub.rn.f16x2 %0, %1, %2;" : "=r"(r) : "r"(a), "r"(b)); return r; }
__device__ __forceinline__ uint32_t hfma2(uint32_t a, uint32_t b, uint32_t c) { uint32_t r; asm("fma.rn.f16x2 %0, %1, %2, %3;" : "=r"(r) : "r"(a), "r"(b), "r"(c)); return r; }
__device__ __forceinline__ uint32_t hamax2(uint32_t a, uint32_t b) { uint32_t r; asm("max.NaN.xorsign.abs.f16x2 %0, %1, %2;" : "=r"(r) : "r"(a), "r"(b)); return r; }
__device__ __forceinline__ uint32_t hmag(uint32_t m) { return max(m & 0x7fffu, (m >> 16) & 0x7fffu); }
__device__ __forceinline__ float bf_lo(uint32_t v) { return __uint_as_float(v << 16); }
__device__ __forceinline__ float bf_hi(uint32_t v) { return __uint_as_float(v & 0xffff0000u); }
__device__ __forceinline__ uint32_t bf2h(uint32_t v) { return pack_h(bf_lo(v), bf_hi(v)); }
__device__ __forceinline__ uint32_t finish2(float z0, float z1, uint32_t x) {
    uint32_t z, o;
    asm("cvt.rn.relu.bf16x2.f32 %0, %1, %2;" : "=r"(z) : "f"(z1), "f"(z0));
    asm("fma.rn.bf16x2 %0, %1, %2, %3;" : "=r"(o) : "r"(z), "r"(0x3b803b80u), "r"(x));
    return o;
}
__device__ __forceinline__ uint32_t opaque32(uint32_t v) { asm volatile("" : "+r"(v)); return v; }
__device__ __forceinline__ uint2 lds64(uint32_t a) { uint2 v; asm volatile("ld.shared.v2.u32 {%0,%1}, [%2];" : "=r"(v.x), "=r"(v.y) : "r"(a)); return v; }
__device__ __forceinline__ uint4 lds128(uint32_t a) {
    uint4 v;
    asm("ld.shared.v4.u32 {%0,%1,%2,%3}, [%4];" : "=r"(v.x), "=r"(v.y), "=r"(v.z), "=r"(v.w) : "r"(a));
    return v;
}

__device__ __forceinline__ void spin_limit(uint32_t it) {
    asm volatile("{\n.reg .pred q;\n.reg .b64 z;\nmov.b64 z, 0;\nsetp.gt.u32 q, %0, 0x400000;\n@q st.global.u32 [z], %0;\n}" ::"r"(it));
}
__device__ __forceinline__ void wg_fence() { asm volatile("wgmma.fence.sync.aligned;" ::: "memory"); }
__device__ __forceinline__ void wg_commit() { asm volatile("wgmma.commit_group.sync.aligned;" ::: "memory"); }
__device__ __forceinline__ void wg_wait() { asm volatile("wgmma.wait_group.sync.aligned 0;" ::: "memory"); }
__device__ __forceinline__ void proxy_fence() { asm volatile("fence.proxy.async.shared::cta;" ::: "memory"); }
__device__ __forceinline__ void cp_commit() { asm volatile("cp.async.commit_group;" ::: "memory"); }
__device__ __forceinline__ void cp_wait() { asm volatile("cp.async.wait_group 0;" ::: "memory"); }
__device__ __forceinline__ void cp16(uint32_t dst, const void* src) { asm volatile("cp.async.cg.shared.global [%0], [%1], 16;" ::"r"(dst), "l"(src) : "memory"); }
template <int ID, int N> __device__ __forceinline__ void bar_sync() { asm volatile("bar.sync %0, %1;" ::"n"(ID), "n"(N) : "memory"); }
template <int ID, int N> __device__ __forceinline__ void bar_arrive() { asm volatile("bar.arrive %0, %1;" ::"n"(ID), "n"(N) : "memory"); }
template <int N> __device__ __forceinline__ void bar_sync(uint32_t id) { asm volatile("bar.sync %0, %1;" ::"r"(id), "n"(N) : "memory"); }
template <int N> __device__ __forceinline__ void bar_arrive(uint32_t id) { asm volatile("bar.arrive %0, %1;" ::"r"(id), "n"(N) : "memory"); }
__device__ __forceinline__ uint32_t ld_relaxed(const uint32_t* p) {
    uint32_t v;
    asm volatile("ld.relaxed.gpu.global.u32 %0, [%1];" : "=r"(v) : "l"(p) : "memory");
    return v;
}
__device__ __forceinline__ void st_relaxed(uint32_t* p, uint32_t v) { asm volatile("st.relaxed.gpu.global.u32 [%0], %1;" ::"l"(p), "r"(v) : "memory"); }
__device__ __forceinline__ uint2 ld_relaxed8(const void* p) {
    uint2 v;
    asm volatile("{\n.reg .b64 t;\nld.relaxed.gpu.global.b64 t, [%2];\nmov.b64 {%0, %1}, t;\n}" : "=r"(v.x), "=r"(v.y) : "l"(p) : "memory");
    return v;
}
__device__ __forceinline__ void st_relaxed8(void* p, uint32_t lo, uint32_t hi) {
    asm volatile("{\n.reg .b64 t;\nmov.b64 t, {%1, %2};\nst.relaxed.gpu.global.b64 [%0], t;\n}" ::"l"(p), "r"(lo), "r"(hi) : "memory");
}
__device__ __forceinline__ void bulk_load(uint32_t dst, const void* src, uint32_t bytes, uint32_t bar) {
    asm volatile("cp.async.bulk.shared::cluster.global.mbarrier::complete_tx::bytes [%0], [%1], %2, [%3];"
                 ::"r"(dst), "l"(src), "r"(bytes), "r"(bar) : "memory");
}
__device__ __forceinline__ void mbar_init(uint32_t bar) { asm volatile("mbarrier.init.shared::cta.b64 [%0], 1;" ::"r"(bar) : "memory"); }
__device__ __forceinline__ void expect_tx(uint32_t bar, uint32_t bytes) {
    asm volatile("mbarrier.arrive.expect_tx.shared::cta.b64 _, [%0], %1;" ::"r"(bar), "r"(bytes) : "memory");
}
__device__ __forceinline__ bool mbar_try(uint32_t bar) {
    uint32_t ok;
    asm volatile("{\n.reg .pred q;\nmbarrier.try_wait.parity.shared::cta.b64 q, [%1], 0;\nselp.u32 %0, 1, 0, q;\n}"
                 : "=r"(ok) : "r"(bar) : "memory");
    return ok;
}
__device__ __forceinline__ void mbar_wait(uint32_t bar) {
    for (uint32_t it = 0; !mbar_try(bar); it++) spin_limit(it);
}
__device__ __forceinline__ void ld_relaxed16_if(uint4& v, const uint4* p, bool on) {
    asm volatile("{\n.reg .pred q;\n.reg .b128 t;\n.reg .b64 a, b;\nsetp.ne.u32 q, %5, 0;\n"
                 "mov.b64 a, {%0, %1};\nmov.b64 b, {%2, %3};\nmov.b128 t, {a, b};\n@q ld.relaxed.gpu.global.b128 t, [%4];\n"
                 "mov.b128 {a, b}, t;\nmov.b64 {%0, %1}, a;\nmov.b64 {%2, %3}, b;\n}"
                 : "+r"(v.x), "+r"(v.y), "+r"(v.z), "+r"(v.w) : "l"(p), "r"((uint32_t)on) : "memory");
}
__device__ __forceinline__ void st_relaxed16(uint4* p, uint4 v) {
    asm volatile("{\n.reg .b128 t;\n.reg .b64 a, b;\nmov.b64 a, {%1, %2};\nmov.b64 b, {%3, %4};\nmov.b128 t, {a, b};\n"
                 "st.relaxed.gpu.global.b128 [%0], t;\n}"
                 ::"l"(p), "r"(v.x), "r"(v.y), "r"(v.z), "r"(v.w) : "memory");
}

#define R4(d, o) "+r"(d[o]), "+r"(d[o + 1]), "+r"(d[o + 2]), "+r"(d[o + 3])
#define L16 "%0,%1,%2,%3,%4,%5,%6,%7,%8,%9,%10,%11,%12,%13,%14,%15"
#define L24 L16 ",%16,%17,%18,%19,%20,%21,%22,%23"
constexpr uint32_t HI_SW = 0x40000000u | 64u;
template <int A>
__device__ __forceinline__ void mma_ss(uint32_t (&d)[24], uint32_t alo, uint32_t blo) {
    asm volatile("{\n.reg .b64 a, b;\nmov.b64 a, {%24, %26};\nmov.b64 b, {%25, %26};\n"
                 "wgmma.mma_async.sync.aligned.m64n96k16.f16.f16.f16 {" L24 "}, a, b, %27, 1, 1, 1, 0;\n}\n"
                 : R4(d, 0), R4(d, 4), R4(d, 8), R4(d, 12), R4(d, 16), R4(d, 20)
                 : "r"(alo), "r"(blo), "r"(HI_SW), "n"(A));
}
template <int A, int T>
__device__ __forceinline__ void mma_rs(uint32_t (&d)[16], const uint32_t* a, uint32_t blo) {
    asm volatile("{\n.reg .b64 b;\nmov.b64 b, {%20, %21};\n"
                 "wgmma.mma_async.sync.aligned.m64n64k16.f16.f16.f16 {" L16 "}, {%16,%17,%18,%19}, b, %22, 1, 1, %23;\n}\n"
                 : R4(d, 0), R4(d, 4), R4(d, 8), R4(d, 12)
                 : "r"(a[0]), "r"(a[1]), "r"(a[2]), "r"(a[3]), "r"(blo), "r"(HI_SW), "n"(A), "n"(T));
}
template <int R> __device__ __forceinline__ void keep(uint32_t (&d)[R]) {
#pragma unroll
    for (int i = 0; i < R; i++) asm volatile("" : "+r"(d[i])::"memory");
}
__device__ __forceinline__ void ldsm_t(uint32_t* f, uint32_t addr) {
    asm volatile("ldmatrix.sync.aligned.m8n8.x4.trans.shared.b16 {%0,%1,%2,%3}, [%4];"
                 : "=r"(f[0]), "=r"(f[1]), "=r"(f[2]), "=r"(f[3]) : "r"(addr) : "memory");
}
__device__ __forceinline__ uint32_t stage_w(unsigned char* mat, int k, int c, uint4 a, uint4 b, float s) {
    unsigned char* row = mat + k * 128;
    const uint4 e = make_uint4(pack_h(s * bf_lo(a.x), s * bf_lo(a.y)), pack_h(s * bf_lo(a.z), s * bf_lo(a.w)),
                               pack_h(s * bf_lo(b.x), s * bf_lo(b.y)), pack_h(s * bf_lo(b.z), s * bf_lo(b.w)));
    const uint4 o = make_uint4(pack_h(s * bf_hi(a.x), s * bf_hi(a.y)), pack_h(s * bf_hi(a.z), s * bf_hi(a.w)),
                               pack_h(s * bf_hi(b.x), s * bf_hi(b.y)), pack_h(s * bf_hi(b.z), s * bf_hi(b.w)));
    *reinterpret_cast<uint4*>(row + ((c ^ (k & 7)) << 4)) = e;
    *reinterpret_cast<uint4*>(row + (((c + 1) ^ (k & 7)) << 4)) = o;
    return hamax2(hamax2(hamax2(e.x, e.y), hamax2(e.z, e.w)), hamax2(hamax2(o.x, o.y), hamax2(o.z, o.w)));
}

struct Params {
    const int* dst;
    const int* src;
    const __nv_bfloat16* e;
    int N, E, npc, chunk;
    const __nv_bfloat16* x;
    __nv_bfloat16* out;
    uint32_t* cnt;
    const __nv_bfloat16 *wa, *wb, *wc, *wu, *wv;
    uint4* cell;
    uint64_t* ext;
    uint32_t* len;
    const uint4* x16;
    uint32_t magic;
};

__device__ __noinline__ void slow_bin(const Params& p, unsigned char* sm, int node0, int nvalid) {
    float* acc = reinterpret_cast<float*>(sm);
    const int tid = threadIdx.x, lane = tid & 31, warp = tid >> 5;
    bar_sync<B_EDGE, NT>();
    for (int i = tid; i < NSLOT * 128; i += NT) acc[i] = 0.f;
    bar_sync<B_EDGE, NT>();
    const uint32_t* x2 = reinterpret_cast<const uint32_t*>(p.x);
    const uint32_t* wb = reinterpret_cast<const uint32_t*>(p.wb) + lane;
    const uint32_t* wv = reinterpret_cast<const uint32_t*>(p.wv) + lane;
    const uint32_t* wa = reinterpret_cast<const uint32_t*>(p.wa) + lane;
    const uint32_t* wu = reinterpret_cast<const uint32_t*>(p.wu) + lane;
    const uint32_t wc = reinterpret_cast<const uint32_t*>(p.wc)[lane];
    for (int i0 = warp * 32; i0 < p.E; i0 += NT) {
        const int dl = i0 + lane < p.E ? p.dst[i0 + lane] - node0 : -1;
        uint32_t m = __ballot_sync(0xffffffffu, (uint32_t)dl < (uint32_t)nvalid);
        while (m) {
            const int l = __ffs(m) - 1;
            m &= m - 1;
            const int d = __shfl_sync(0xffffffffu, dl, l);
            const uint32_t xs = x2[p.src[i0 + l] * 32 + lane], xd = x2[(node0 + d) * 32 + lane];
            float g0 = 0.f, g1 = 0.f, v0 = 0.f, v1 = 0.f;
#pragma unroll 4
            for (int k = 0; k < 32; k++) {
                const uint32_t a = __shfl_sync(0xffffffffu, xs, k), b = __shfl_sync(0xffffffffu, xd, k);
#pragma unroll
                for (int h = 0; h < 2; h++) {
                    const float fs = h ? bf_hi(a) : bf_lo(a), fd = h ? bf_hi(b) : bf_lo(b);
                    const uint32_t ua = wa[(2 * k + h) * 32], ub = wb[(2 * k + h) * 32], uv = wv[(2 * k + h) * 32];
                    g0 += fd * bf_lo(ua) + fs * bf_lo(ub);
                    g1 += fd * bf_hi(ua) + fs * bf_hi(ub);
                    v0 += fs * bf_lo(uv);
                    v1 += fs * bf_hi(uv);
                }
            }
            const float ev = __bfloat162float(p.e[i0 + l]);
            const float e0 = rcp(1.f + __expf(-(g0 + ev * bf_lo(wc))));
            const float e1 = rcp(1.f + __expf(-(g1 + ev * bf_hi(wc))));
            float* a = acc + d * 128 + 2 * lane;
            atomicAdd(a, e0);
            atomicAdd(a + 1, e1);
            atomicAdd(a + 64, e0 * v0);
            atomicAdd(a + 65, e1 * v1);
        }
    }
    bar_sync<B_EDGE, NT>();
    for (int n = warp; n < nvalid; n += NW) {
        const uint32_t xd = x2[(node0 + n) * 32 + lane];
        float u0 = 0.f, u1 = 0.f;
#pragma unroll 4
        for (int k = 0; k < 32; k++) {
            const uint32_t b = __shfl_sync(0xffffffffu, xd, k);
            const uint32_t w0 = wu[(2 * k) * 32], w1 = wu[(2 * k + 1) * 32];
            u0 += bf_lo(b) * bf_lo(w0) + bf_hi(b) * bf_lo(w1);
            u1 += bf_lo(b) * bf_hi(w0) + bf_hi(b) * bf_hi(w1);
        }
        const float* a = acc + n * 128 + 2 * lane;
        const float z0 = u0 + a[64] * rcp(a[0] + 1e-6f), z1 = u1 + a[65] * rcp(a[1] + 1e-6f);
        const float r0 = z0 > 0.f ? z0 : 0.f * z0, r1 = z1 > 0.f ? z1 : 0.f * z1;
        reinterpret_cast<uint32_t*>(p.out)[(node0 + n) * 32 + lane] = pack_bf16(bf_lo(xd) + r0, bf_hi(xd) + r1);
    }
}

__device__ __noinline__ void redo_small(const void* px, const void* pwb, const void* pwv, const void* pwc, void* pout,
                                        uint32_t flags, int wg, int node0) {
    extern __shared__ __align__(1024) unsigned char sm[];
    const int lane = threadIdx.x & 31, g = lane >> 2, t = lane & 3;
    uint32_t i0 = 0;
    float den = 0.f, num = 0.f;
#pragma unroll 1
    for (uint32_t m; (m = __ballot_sync(0xffffffffu, flags != 0)) != 0;) {
        const int l = __ffs(m) - 1;
        const uint32_t k = __ffs(__shfl_sync(0xffffffffu, flags, l)) - 1;
        const uint32_t pr = ((threadIdx.x >> 5) & 3) * 8 + (l >> 2);
        const uint32_t ta = reinterpret_cast<const uint2*>(sm + SM_GI)[(wg * GPW + (k & 15) - (16 - GPW)) * 8 + 2 * (l & 3) + (k >> 4)].x;
        const uint32_t n = (ta - SB - SM_TBL) >> 8;
        const uint32_t deg = reinterpret_cast<const uint32_t*>(sm + SM_DEG)[n];
        const uint32_t base = (reinterpret_cast<const uint32_t*>(sm + SM_CUR)[n] >> 2) - 8 * deg;
        const uint2 tb = lds64(ta ^ (pr * 8));
        uint4 xr[4][2];
        uint32_t en[4], wr[16];
#pragma unroll
        for (int u = 0; u < 4; u++) {
            en[u] = reinterpret_cast<const uint32_t*>(sm + SM_ENT)[base + 8 * min(i0 + 8 * u + g, max(deg, 1u) - 1)];
            xr[u][0] = __ldg(reinterpret_cast<const uint4*>(px) + (en[u] & 0xffff) * 8 + 2 * t);
            xr[u][1] = __ldg(reinterpret_cast<const uint4*>(px) + (en[u] & 0xffff) * 8 + 2 * t + 1);
        }
        const uint16_t* w = reinterpret_cast<const uint16_t*>((g & 1) ? pwv : pwb) + 16 * t * 64 + 2 * pr + ((g >> 1) & 1);
#pragma unroll
        for (int i = 0; i < 16; i++) wr[i] = __ldg(w + i * 64);
        uint32_t x;
        asm volatile("ld.volatile.global.u32 %0, [%1];" : "=r"(x) : "l"(reinterpret_cast<const uint32_t*>(px) + (node0 + n) * 32 + pr));
        const float wc = bf_lo(__ldg(reinterpret_cast<const uint16_t*>(pwc) + 2 * pr + (t & 1)));
        const float a = 2.f * ((t & 1) ? h_hi(tb.x) : h_lo(tb.x));
#pragma unroll
        for (int u = 0; u < 4; u += 2) {
            float c[4] = {0.f, 0.f, 0.f, 0.f};
#pragma unroll
            for (int q = 0; q < 4; q++) {
                const uint4 r0 = xr[u][q >> 1], r1 = xr[u + 1][q >> 1];
                asm("mma.sync.aligned.m16n8k16.row.col.f32.bf16.bf16.f32 {%0,%1,%2,%3}, {%4,%5,%6,%7}, {%8,%9}, {%0,%1,%2,%3};"
                    : "+f"(c[0]), "+f"(c[1]), "+f"(c[2]), "+f"(c[3])
                    : "r"((q & 1) ? r0.z : r0.x), "r"((q & 1) ? r1.z : r1.x), "r"((q & 1) ? r0.w : r0.y), "r"((q & 1) ? r1.w : r1.y),
                      "r"(wr[4 * q] | wr[4 * q + 1] << 16), "r"(wr[4 * q + 2] | wr[4 * q + 3] << 16));
            }
#pragma unroll
            for (int h = 0; h < 2; h++) {
                float eta = rcp(1.f + __expf(-(a + c[2 * h] + h_hi(en[u + h]) * wc)));
                eta = i0 + 8 * (u + h) + g < deg ? eta : 0.f;
                den += eta;
                num += eta * c[2 * h + 1];
            }
        }
        i0 += 32;
        if (i0 >= deg) {
#pragma unroll
            for (int o = 4; o < 32; o <<= 1) { den += __shfl_xor_sync(0xffffffffu, den, o); num += __shfl_xor_sync(0xffffffffu, num, o); }
            const float agg = 256.f * num * rcp(den + 1e-6f);
            const uint32_t o = finish2(__shfl_sync(0xffffffffu, agg, 0) + h_lo(tb.y), __shfl_sync(0xffffffffu, agg, 1) + h_hi(tb.y), x);
            if (lane == l) {
                if (!(ta & 8)) reinterpret_cast<uint32_t*>(pout)[(node0 + n) * 32 + pr] = o;
                flags &= flags - 1;
            }
            i0 = 0; den = 0.f; num = 0.f;
        }
    }
}

template <int MODE>
__global__ void __launch_bounds__(NTA, 1) gatedgcn_kernel(const __grid_constant__ Params p, const __grid_constant__ CUtensorMap xmap,
                                                          const __grid_constant__ CUtensorMap hmap) {
    extern __shared__ __align__(1024) unsigned char sm[];
    constexpr uint32_t sb = SB;
    spin_limit((uint32_t)__cvta_generic_to_shared(sm) != SB ? ~0u : 0u);
    const int tid = threadIdx.x, lane = tid & 31;
    const int warp = __shfl_sync(0xffffffffu, tid >> 5, 0);
    const int wg = warp >> 2, w4 = warp & 3, g8 = lane >> 2, t4 = lane & 3, tw = tid & 127;
    const int cta = blockIdx.x;
    const int node0 = cta * p.npc;
    const int nvalid = min(p.npc, p.N - node0);
    const int ch = 16 * w4 + 2 * g8;
    const uint32_t share = cta == 0 ? 1024 - G + 1 : 1;

    uint32_t* s_hist = reinterpret_cast<uint32_t*>(sm + SM_HIST);
    uint32_t* s_deg = reinterpret_cast<uint32_t*>(sm + SM_DEG);
    uint32_t* s_cur = reinterpret_cast<uint32_t*>(sm + SM_CUR);
    uint2* s_gi = reinterpret_cast<uint2*>(sm + SM_GI);
    uint32_t* s_dh = reinterpret_cast<uint32_t*>(sm + SM_DH);
    uint32_t* s_lg = reinterpret_cast<uint32_t*>(sm + SM_LG);
    uint32_t* s_end = reinterpret_cast<uint32_t*>(sm + SM_END);
    uint32_t* s_misc = reinterpret_cast<uint32_t*>(sm + SM_MISC);
    uint32_t* s_ent = reinterpret_cast<uint32_t*>(sm + SM_ENT);
    auto max_tiles = [&]() {
        uint32_t tm = 0;
#pragma unroll
        for (int k = 0; k < NWG; k++) tm = max(tm, (s_misc[M_STEP0 + 1 + k] - s_misc[M_STEP0 + k] + NSTEP - 1) / NSTEP);
        return tm;
    };

    if (wg == NWG) {
        if (tw == 0) {
#pragma unroll
            for (int i = 0; i < 4; i++) mbar_init(sb + SM_LBAR + 8 * i);
            proxy_fence();
            if (MODE & 2) {
                expect_tx(sb + SM_LBAR + 24, 4 * 8192 + 128);
                bulk_load(sb + SM_W, p.wa, 8192, sb + SM_LBAR + 24);
                bulk_load(sb + SM_W + 8192, p.wu, 8192, sb + SM_LBAR + 24);
                bulk_load(sb + SM_W + 16384, p.wb, 8192, sb + SM_LBAR + 24);
                bulk_load(sb + SM_W + 24576, p.wv, 8192, sb + SM_LBAR + 24);
                bulk_load(sb + SM_WC, p.wc, 128, sb + SM_LBAR + 24);
            }
        }
        asm volatile("setmaxnreg.dec.sync.aligned.u32 32;");
        uint32_t mw = 0;
        if (MODE & 2) {
            {
                const int k = (tw >> 3) & 7;
                const uint32_t one = tw >= 64 ? 0x3c00u << (16 * (k & 1)) : 0u;
                const uint4 v = make_uint4(k >> 1 == 0 ? one : 0, k >> 1 == 1 ? one : 0, k >> 1 == 2 ? one : 0, k >> 1 == 3 ? one : 0);
                reinterpret_cast<uint4*>(sm + SM_EXT)[tw] = v;
                reinterpret_cast<uint4*>(sm + SM_EXT)[tw + 128] = v;
            }
            bar_sync<1 + NWG, 128>();
            mbar_wait(sb + SM_LBAR + 24);
            if (w4 == 0) {
                mw = reinterpret_cast<uint32_t*>(sm + SM_WC)[lane];
                mw = pack_h(0.5f * bf_lo(mw), 0.5f * bf_hi(mw));
                reinterpret_cast<uint32_t*>(sm + SM_WC)[lane] = mw;
                mw = hmag(mw);
            }
#pragma unroll 1
            for (int j = 0; j < 8; j++) {
                const uint4* w = reinterpret_cast<const uint4*>(sm + SM_W + j * 4096) + tw * 2;
                const uint4 a = w[0], b = w[1];
                __syncwarp();
                const uint32_t m = hmag(stage_w(sm + SM_W + j * 4096, tw >> 2, (tw & 3) * 2, a, b, (j & 2) ? 256.f : 0.5f));
                mw = max((int)mw, (int)m - ((j & 2) ? 8 << 10 : 0));
            }
        }
        proxy_fence();
        bar_sync<B_SENT, NTA>();
        const uint32_t epoch = s_misc[M_EPOCH];
        if (mw > H_MAX) s_misc[M_RANGE] = 1;
        if (w4 == 0) {
            if (MODE & 2) {
                if (MODE == 3 && lane == 0) for (uint32_t it = 0; ld_relaxed(p.cnt) != epoch << 10; it++) spin_limit(it);
                __syncwarp();
                bar_arrive<B_READY, 128>();
            }
            if ((MODE & 2) && lane == 0) {
                const uint4* in = p.cell + cta * G * CV;
                proxy_fence();
                expect_tx(sb + SM_LBAR, LND);
                bulk_load(sb + SM_ENT, in, LND, sb + SM_LBAR);
                expect_tx(sb + SM_LBAR + 8, LND);
                bulk_load(sb + SM_ENT + LND, in + LND / 16, LND, sb + SM_LBAR + 8);
                expect_tx(sb + SM_LBAR + 16, G * CV * 16 - 2 * LND);
                bulk_load(sb + SM_LND2, in + LND / 8, G * CV * 16 - 2 * LND, sb + SM_LBAR + 16);
            }
            if (MODE & 1) bar_sync<B_CONV, NT + 32>();
            if (MODE == 3) mbar_wait(sb + SM_LBAR + 8);
            if (lane == 0) {
                if (MODE & 1) {
#pragma unroll 1
                    for (int b = 0; b < NWG; b++)
                        asm volatile("cp.async.bulk.tensor.2d.global.shared::cta.bulk_group [%0, {%2, %3}], [%1];"
                                     ::"l"(&hmap), "r"(sb + SM_RING + b * XROWS * 128), "r"(0), "r"(node0 + b * XROWS) : "memory");
                    asm volatile("cp.async.bulk.commit_group;" ::: "memory");
                    if (s_misc[M_XBAD]) st_relaxed(p.cnt + 33, epoch);
                    asm volatile("cp.async.bulk.wait_group 0;" ::: "memory");
                    asm volatile("red.release.gpu.global.add.u32 [%0], %1;" ::"l"(p.cnt + 32), "r"(share) : "memory");
                }
                if (MODE & 2) {
                    uint2 c = ld_relaxed8(p.cnt + 32);
                    for (uint32_t it = 0; c.x != epoch << 10; it++) { c = ld_relaxed8(p.cnt + 32); spin_limit(it); }
                    asm volatile("fence.acquire.gpu;" ::: "memory");
                    if (c.y == epoch) s_misc[M_LATE] = 1;
                }
            }
            __syncwarp();
        } else if (MODE & 2) {
            const uint32_t tag23 = epoch << 9;
            const int t = tw - 32;
            const int c0 = (w4 - 1) * (G / 3);
            uint32_t ln[2] = {~tag23, lane < G / 3 - 32 ? ~tag23 : tag23};
            for (uint32_t it = 0; ((ln[0] ^ tag23) | (ln[1] ^ tag23)) > 0x1ff; it++) {
#pragma unroll
                for (int r = 0; r < 2; r++)
                    if ((ln[r] ^ tag23) > 0x1ff) ln[r] = ld_relaxed(p.len + cta * LSTR + c0 + lane + 32 * r);
                spin_limit(it);
            }
            __syncwarp();
            uint32_t at[TPL] = {}, nt = 0;
#pragma unroll
            for (int r = 0; r < 2; r++) {
                const uint32_t len = ln[r] & 0x1ff;
                if (len > CAPC) s_misc[M_NOFIT] = 1;
                for (uint32_t m = __ballot_sync(0xffffffffu, len > 3 * CV && len <= CAPC); m; m &= m - 1) {
                    const uint32_t l = __ffs(m) - 1;
#pragma unroll
                    for (int k = 0; k < TPL; k++)
                        if (lane + 32 * k >= nt) at[k] = (c0 + l + 32 * r) * CX + lane + 32 * k - nt;
                    nt += __reduce_max_sync(0xffffffffu, lane == l ? len : 0) - 3 * CV;
                }
            }
            if (nt > 32 * TPL) s_misc[M_NOFIT] = 1;
            uint2 v[TPL];
#pragma unroll
            for (int k = 0; k < TPL; k++) v[k] = make_uint2(0, lane + 32 * k < nt ? ~tag23 : tag23 | 511);
            bar_sync<B_READY, 128>();
            for (uint32_t it = 0; ((v[0].y ^ tag23) | (v[1].y ^ tag23) | (v[2].y ^ tag23) | (v[3].y ^ tag23)) > 0x1ff; it++) {
#pragma unroll
                for (int k = 0; k < TPL; k++)
                    if ((v[k].y ^ tag23) > 0x1ff) v[k] = ld_relaxed8(p.ext + cta * G * CX + at[k]);
                spin_limit(it);
            }
            __syncwarp();
#pragma unroll
            for (int k = 0; k < TPL; k++) atomicAdd(&s_deg[v[k].y & 0x1ff], 1u);
            bar_sync<B_COUNT, NT + 96>();
            const uint32_t pv = node0 | E_PAD;
            for (int k = t; k < CAPX / 4; k += 96) reinterpret_cast<uint4*>(s_ent)[k] = make_uint4(pv, pv, pv, pv);
            bar_sync<B_SORT, NT + 96>();
            if (s_misc[M_SKIP] == 0) {
#pragma unroll
                for (int k = 0; k < TPL; k++)
                    if (lane + 32 * k < nt) s_ent[atomicAdd(&s_cur[v[k].y & 0x1ff], 32u) >> 2] = v[k].x;
            }
        }
        if (!(MODE & 2)) return;
        if (w4 != 0) bar_sync<B_GO, NT + 96>(); else bar_sync<B_ROWS, 128>();
        if (s_misc[M_SKIP] | s_misc[M_RANGE] | (s_misc[M_XBIG] ^ 1)) {
            if (w4 != 0) bar_arrive<B_ROWS, 128>(); else bar_arrive<0, NT + 32>();
            return;
        }
        const int fw = (w4 + 3) & 3;
        const uint32_t step0 = s_misc[M_STEP0 + fw];
        const int T = (s_misc[M_STEP0 + 1 + fw] - step0 + NSTEP - 1) / NSTEP;
        const int q = lane >> 3, c8 = lane & 7;
        uint32_t sidx = sb + SM_ENT + step0 * 32 + q * 8;
        uint32_t sd0 = sb + SM_RING + fw * (2 * TB) + q * 256 + ((c8 ^ (2 * q)) << 4);
        uint32_t se = sb + SM_EXT + fw * 256 + ((c8 ^ (2 * fw)) << 4) + q * 4;
        const uint32_t xlo = (uint32_t)reinterpret_cast<uint64_t>(p.x16) + c8 * 16;
        const uint32_t xhi = (uint32_t)(reinterpret_cast<uint64_t>(p.x16) >> 32);
#pragma unroll 1
        for (int i = 0; i < T; i++) {
            uint2 nx[NSTEP];
            const uint2 ee = lds64(sidx + 32 * c8);
#pragma unroll
            for (int j = 0; j < NSTEP; j++) nx[j] = lds64(sidx + 32 * j);
            const uint32_t e2 = __byte_perm(ee.x, ee.y, 0x7632);
            uint32_t pm;
            asm("set.nan.u32.f16x2 %0, %1, %1;" : "=r"(pm) : "r"(e2));
            if (i > 0) {
                cp_wait();
                proxy_fence();
                bar_sync<288>(1 + fw);
            } else if (w4 != 0) {
                bar_sync<B_ROWS, 128>();
            }
            asm volatile("st.shared.u32 [%0], %1;" ::"r"(se), "r"(e2 & ~pm) : "memory");
            asm volatile("st.shared.u32 [%0+128], %1;" ::"r"(se ^ 16), "r"(pm & 0x40004000u) : "memory");
#pragma unroll
            for (int u = 0; u < 2 * NSTEP; u++) {
                uint64_t ga;
                asm("{\n.reg .b32 lo;\ndp2a.lo.u32.u32 lo, %1, 0x80, %2;\nmov.b64 %0, {lo, %3};\n}"
                    : "=l"(ga) : "r"((u & 1) ? nx[u >> 1].y : nx[u >> 1].x), "r"(xlo), "r"(xhi));
                cp16((sd0 ^ ((u & 1) * 16)) + (u & 1) * 128 + (u >> 1) * 1024, reinterpret_cast<const void*>(ga));
            }
            cp_commit();
            sidx += NSTEP * 32;
            sd0 ^= TB;
            se ^= 2048;
        }
        cp_wait();
        proxy_fence();
        for (uint32_t i = T - 1, n = max_tiles() + (fw == 0); i < n; i++) bar_sync<288>(1 + fw);
    } else {
        const uint32_t bar = sb + SM_BAR + wg * 24;
        const int e0 = cta * p.chunk + wg * VWG * 4;
        const int nvec = min(min(p.chunk - wg * VWG * 4, p.E - e0) >> 2, VWG);
        auto load_x = [&]() {
            if (tw == 0) {
                expect_tx(bar + 16, XROWS * 128);
                asm volatile("cp.async.bulk.tensor.2d.shared::cluster.global.mbarrier::complete_tx::bytes [%0], [%1, {%3, %4}], [%2];"
                             ::"r"(sb + SM_RING + wg * XROWS * 128), "l"(&xmap), "r"(bar + 16), "r"(0), "r"(node0 + wg * XROWS) : "memory");
            }
        };
        if (tw == 0) {
#pragma unroll
            for (int i = 0; i < 3; i++) mbar_init(bar + i * 8);
            proxy_fence();
            if (MODE & 1) {
                expect_tx(bar, nvec * 16);
                bulk_load(sb + SM_RING + wg * XROWS * 128, p.dst + e0, nvec * 16, bar);
            }
        }
        if (MODE == 2) load_x();
        const uint32_t cnt0 = ld_relaxed(p.cnt + opaque32(0));

        if (tid < (SM_CUR - SM_DEG) / 16) reinterpret_cast<uint4*>(sm + SM_DEG)[tid] = make_uint4(0, 0, 0, 0);
        if (tid < 32) s_cur[NSLOT + tid] = 0x80000000u;
        if (tid < 8) s_gi[NWG * GPW * 8 + tid] = make_uint2(sb + SM_TBL, 0);
        if (MODE & 1) {
#pragma unroll
            for (int j = 0; j < (G * CAPC / 2 + NT - 1) / NT; j++)
                if (tid + NT * j < G * CAPC / 2) reinterpret_cast<uint4*>(sm + SM_TBL)[tid + NT * j] = make_uint4(0, 511, 0, 511);
            if (tw == 0) {
                expect_tx(bar + 8, nvec * 24);
                bulk_load(sb + SM_ENT + wg * VWG * 24, p.src + e0, nvec * 16, bar + 8);
                bulk_load(sb + SM_ENT + wg * VWG * 24 + VWG * 16, p.e + e0, nvec * 8, bar + 8);
            }
        }
        bar_sync<B_EDGE, NT>();

        const uint32_t epoch = (cnt0 >> 10) + (MODE == 2 ? 0 : 1);
        const uint32_t tag5 = epoch << 27, tag23 = epoch << 9;
        if (MODE & 1) {
            int4 dv[VPT];
            mbar_wait(bar);
#pragma unroll
            for (int j = 0; j < VPT; j++) dv[j] = reinterpret_cast<const int4*>(sm + SM_RING + wg * XROWS * 128)[tw + 128 * j];
            uint32_t key[VPT * 4];
#pragma unroll
            for (int j = 0; j < VPT; j++) {
                const bool ok = tw + 128 * j < nvec;
                const int d[4] = {dv[j].x, dv[j].y, dv[j].z, dv[j].w};
#pragma unroll
                for (int q = 0; q < 4; q++) {
                    const uint32_t b = ok ? __umulhi((uint32_t)d[q], p.magic) : G;
                    const uint32_t r = atomicAdd(&s_hist[b], 1u);
                    key[j * 4 + q] = (b * CAPC + min(r, CAPC - 1u)) | ((uint32_t)(d[q] - b * p.npc) << 16);
                }
            }
            proxy_fence();
            bar_sync<B_EDGE, NT>();
            if (tid < G) {
                st_relaxed(p.len + tid * LSTR + cta, min(s_hist[tid], 511u) | tag23);
                if (cta < (-G & 7)) p.len[tid * LSTR + G + cta] = 0;
            }
            mbar_wait(bar + 8);
            load_x();
            uint2* stage = reinterpret_cast<uint2*>(sm + SM_TBL);
            uint32_t emax = 0;
#pragma unroll
            for (int j = 0; j < VPT; j++) {
                const uint4 sv = reinterpret_cast<const uint4*>(sm + SM_ENT + wg * VWG * 24)[tw + 128 * j];
                uint2 ev = reinterpret_cast<const uint2*>(sm + SM_ENT + wg * VWG * 24 + VWG * 16)[tw + 128 * j];
                ev.x = bf2h(ev.x); ev.y = bf2h(ev.y);
                if (tw + 128 * j < nvec) emax = hamax2(emax, hamax2(ev.x, ev.y));
                const uint32_t w0[4] = {__byte_perm(sv.x, ev.x, 0x5410), __byte_perm(sv.y, ev.x, 0x7610),
                                        __byte_perm(sv.z, ev.y, 0x5410), __byte_perm(sv.w, ev.y, 0x7610)};
#pragma unroll
                for (int q = 0; q < 4; q++) stage[key[j * 4 + q] & 0xffff] = make_uint2(w0[q], key[j * 4 + q] >> 16);
            }
            if (hmag(emax) > H_MAX) {
#pragma unroll
                for (int k = 0; k < VPT * 4; k++) stage[key[k] & 0xffff].y = 510;
            }
            bar_sync<B_EDGE, NT>();
            {
                const int b = warp + NW * lane;
                const uint32_t c = b < G ? s_hist[b] : 0;
                for (uint32_t m = __ballot_sync(0xffffffffu, c > 3 * CV); m; m &= m - 1) {
                    const int l = __ffs(m) - 1, bl = warp + NW * l;
                    if (3 * CV + (lane & ~3) < __shfl_sync(0xffffffffu, c, l)) {
                        const uint2 v = stage[bl * CAPC + 3 * CV + lane];
                        st_relaxed8(p.ext + (bl * G + cta) * CX + lane, v.x, v.y | tag23);
                    }
                }
            }
            if (tid < BPR * CV) {
                const int xb = tid / CV, xi = tid - xb * CV;
                const uint2* st = stage + xb * CAPC + xi * 3;
                uint4* gc = p.cell + (xb * G + cta) * CV + xi;
                uint4 v[RND];
#pragma unroll
                for (int j = 0; j < RND; j++)
                    if (xb + BPR * j < G) {
                        const uint2 a = st[j * BPR * CAPC], b = st[j * BPR * CAPC + 1], c = st[j * BPR * CAPC + 2];
                        v[j] = make_uint4(a.x, b.x, c.x, a.y + b.y * 512 + c.y * 262144 + tag5);
                    }
#pragma unroll
                for (int j = 0; j < RND; j++)
                    if (xb + BPR * j < G) {
                        st_relaxed16(gc + j * BPR * G * CV, v[j]);
                        if (j == 2 && tid == NT - 32) asm volatile("red.relaxed.gpu.global.add.u32 [%0], %1;" ::"l"(p.cnt), "r"(share) : "memory");
                    }
            }
        }
        if (tid == 0) s_misc[M_EPOCH] = epoch;
        bar_sync<B_SENT, NTA>();
        asm volatile("setmaxnreg.inc.sync.aligned.u32 112;");
        {
            mbar_wait(bar + 16);
            uint4* xs = reinterpret_cast<uint4*>(sm + SM_RING + wg * XROWS * 128) + tw;
            uint4 v[XROWS / 16];
            uint32_t mx = 0, my = 0;
#pragma unroll
            for (int j = 0; j < XROWS / 16; j++) v[j] = xs[128 * j];
#pragma unroll
            for (int j = 0; j < XROWS / 16; j++) {
                v[j].x = bf2h(v[j].x); v[j].y = bf2h(v[j].y); v[j].z = bf2h(v[j].z); v[j].w = bf2h(v[j].w);
                xs[128 * j] = v[j];
                mx = hfma2(v[j].x, v[j].x, hfma2(v[j].z, v[j].z, mx));
                my = hfma2(v[j].y, v[j].y, hfma2(v[j].w, v[j].w, my));
            }
            if (hmag(hamax2(mx, my)) > SQ_MAX) s_misc[M_XBAD] = 1;
            if (hmag(hamax2(mx, my)) >= SQ_MIN) s_misc[M_XBIG] = 1;
            proxy_fence();
            if (MODE & 1) bar_arrive<B_CONV, NT + 32>();
            if (!(MODE & 2)) return;
            bar_sync<128>(1 + wg);
        }
        uint32_t da[24], du[24];
        {
            const uint32_t dx = (1u << 16) | ((sb + SM_RING + wg * XROWS * 128) >> 4);
            constexpr uint32_t dw = (1u << 16) | ((sb + SM_W) >> 4);
            wg_fence();
            mma_ss<0>(da, dw, dx);
            mma_ss<0>(du, dw + 512, dx);
#pragma unroll
            for (int k = 1; k < 4; k++) { mma_ss<1>(da, dw + 128 * k, dx + 2 * k); mma_ss<1>(du, dw + 512 + 128 * k, dx + 2 * k); }
            wg_commit();
            wg_wait();
            keep(da); keep(du);
        }
        auto table = [&]() {
            unsigned char* tb = sm + SM_TBL + (wg * XROWS + 2 * t4) * 256 + ((ch * 4) ^ (t4 << 5));
            uint32_t am = 0;
#pragma unroll
            for (int j = 0; j < 12; j++) {
                am = hamax2(am, hamax2(da[2 * j], da[2 * j + 1]));
#pragma unroll
                for (int h = 0; h < 2; h++)
                    if (j < 11 || wg * XROWS + 8 * j + 2 * t4 + h < NROW)
                        *reinterpret_cast<uint2*>(tb + (8 * j + h) * 256) =
                            make_uint2(__byte_perm(da[2 * j], da[2 * j + 1], h ? 0x7632 : 0x5410), __byte_perm(du[2 * j], du[2 * j + 1], h ? 0x7632 : 0x5410));
            }
            if (hmag(am) > A_MAX) s_misc[M_RANGE] = 1;
        };
        if (wg < NWG - 1) table();
        uint4 en[RNC];
        uint32_t d4[RNC * 3];
        auto count = [&](int j0, int j1) {
            mbar_wait(sb + SM_LBAR + 4 * j0);
#pragma unroll
            for (int j = j0; j < j1; j++) {
                if (j < RNC - 1 || tid + j * NT < G * CV) en[j] = reinterpret_cast<const uint4*>(sm + (j < 4 ? SM_ENT : SM_LND2 - 2 * LND))[j * NT + tid];
                else en[j] = make_uint4(0, 0, 0, tag5 | 0x7ffffffu);
            }
            for (uint32_t it = 0;; it++) {
                uint32_t miss = 0;
#pragma unroll
                for (int j = j0; j < j1; j++) miss |= en[j].w ^ tag5;
                if (miss < (1u << 27)) break;
#pragma unroll
                for (int j = j0; j < j1; j++)
                    ld_relaxed16_if(en[j], p.cell + cta * G * CV + tid + j * NT, (en[j].w ^ tag5) >= (1u << 27));
                spin_limit(it);
            }
            __syncwarp();
#pragma unroll
            for (int j = j0; j < j1; j++)
#pragma unroll
                for (int s = 0; s < 3; s++) {
                    d4[3 * j + s] = (s == 0 ? en[j].w << 2 : en[j].w >> (9 * s - 2)) & 0x7fc;
                    asm volatile("red.shared.add.u32 [%0+%1], 1;" ::"r"(d4[3 * j + s]), "n"(sb + SM_DEG) : "memory");
                }
        };
        count(0, 2);
        count(2, 4);
        count(4, RNC);
        bar_sync<B_COUNT, NT + 96>();
        uint32_t unused = 0;
        if (warp < NSLOT / 32) {
            const uint32_t dg = s_deg[tid];
            if (dg > 62 || s_deg[510]) s_misc[M_NOFIT] = 1;
            const uint32_t kb = tid < nvalid ? 62 - min(dg, 62u) : 63;
            const uint32_t r = atomicAdd(&s_dh[kb], 1u);
            bar_sync<B_NODE, NSLOT>();
            const uint2 h = reinterpret_cast<const uint2*>(s_dh)[lane];
            uint32_t inc = h.x + h.y;
#pragma unroll
            for (int o = 1; o < 32; o <<= 1) { const uint32_t v = __shfl_up_sync(0xffffffffu, inc, o); if (lane >= o) inc += v; }
            const uint32_t pe = __shfl_sync(0xffffffffu, inc - h.x - h.y, kb >> 1), po = __shfl_sync(0xffffffffu, inc - h.y, kb >> 1);
            const uint32_t pos = ((kb & 1) ? po : pe) + r;
            const uint32_t grp = pos >> 3, slot = pos & 7, row = grp / NWG, col = grp - row * NWG;
            const uint32_t seg = (row & 1) ? NWG - 1 - col : col;
            const uint32_t idx = seg * GPW + GPW - 1 - row;
            if (slot == 0) s_lg[idx] = max(dg, (uint32_t)NSTEP);
            bar_sync<B_NODE, NSLOT>();
            const uint2 l = reinterpret_cast<const uint2*>(s_lg)[lane];
            uint32_t in2 = l.x + l.y;
#pragma unroll
            for (int o = 1; o < 32; o <<= 1) { const uint32_t v = __shfl_up_sync(0xffffffffu, in2, o); if (lane >= o) in2 += v; }
            const uint32_t ex2 = in2 - l.x - l.y;
            const uint32_t mine = __shfl_sync(0xffffffffu, ex2, (lane / (GPW / 2)) * (GPW / 2));
            const uint32_t ee = __shfl_sync(0xffffffffu, in2 - l.y, idx >> 1), eo = __shfl_sync(0xffffffffu, in2, idx >> 1);
            const uint32_t sbeg = __shfl_sync(0xffffffffu, ex2, seg * (GPW / 2));
            if (__any_sync(0xffffffffu, in2 > CAP / 8 || in2 - mine > MAXT * NSTEP) || s_misc[M_NOFIT] != 0) {
                s_misc[M_SKIP] = 1;
            } else {
                const uint32_t gend = (idx & 1) ? eo : ee;
                s_cur[tid] = (gend - dg) * 32 + slot * 4;
                if (tid < nvalid) s_gi[idx * 8 + slot] = make_uint2(sb + SM_TBL + tid * 256 + (((tid >> 1) & 3) << 5), (node0 + tid) * 128);
                else unused = (idx * 8 + slot) | ((seg * GPW + GPW - 1) * 8 + slot) << 16;
                if (slot == 0) {
                    const uint32_t last = gend - 1 - sbeg;
                    s_end[seg * MAXT + last / NSTEP] = last % NSTEP + 1;
                }
                if (tid <= NWG * (GPW / 2) && tid % (GPW / 2) == 0) s_misc[M_STEP0 + tid / (GPW / 2)] = ex2;
            }
        } else {
            table();
        }
        bar_sync<B_SORT, NT + 96>();
        if (s_misc[M_SKIP] == 0) {
            if (unused) { const uint2 v = s_gi[unused >> 16]; s_gi[unused & 0xffff] = make_uint2(v.x ^ 8, v.y); }
            auto place = [&](int j1) {
#pragma unroll
                for (int k = 0; k < 3 * j1; k++)
                    asm volatile("atom.shared.add.u32 %0, [%1+%2], 32;" : "=r"(d4[k]) : "r"(min(d4[k], (NSLOT + lane) * 4u)), "n"(sb + SM_CUR) : "memory");
#pragma unroll
                for (int j = 0; j < j1; j++)
#pragma unroll
                    for (int s = 0; s < 3; s++)
                        asm volatile("{\n.reg .pred q;\nsetp.ge.s32 q, %0, 0;\n@q st.shared.u32 [%0+%2], %1;\n}"
                                     ::"r"(d4[3 * j + s]), "r"(s == 0 ? en[j].x : s == 1 ? en[j].y : en[j].z), "n"(sb + SM_ENT));
            };
            if (warp * 32 + (RNC - 1) * NT < G * CV) place(RNC); else place(RNC - 1);
        }
        bar_sync<B_GO, NT + 96>();
        uint32_t plain = s_misc[M_SKIP] | s_misc[M_RANGE] | (s_misc[M_XBIG] ^ 1);
        if (plain) {
            bar_sync<0, NT + 32>();
        } else {
            __nanosleep(wg * 120);
            uint32_t fb[16], fv[16], fe[4];
            {
                const uint32_t a = sb + SM_W + 16384 + ((lane >> 4) * 8 + (lane & 7)) * 128 + (((2 * w4 + ((lane >> 3) & 1)) ^ (lane & 7)) << 4);
#pragma unroll
                for (int k = 0; k < 4; k++) {
                    ldsm_t(fb + 4 * k, a + k * 2048);
                    ldsm_t(fv + 4 * k, a + 8192 + k * 2048);
                }
                const uint32_t wh = reinterpret_cast<const uint32_t*>(sm + SM_WC)[ch >> 1];
                fe[0] = t4 != wg ? 0 : __byte_perm(wh, 0xfb53, 0x5410);
                fe[1] = t4 != wg ? 0 : __byte_perm(wh, 0xfb53, 0x5432);
                fe[2] = fe[3] = 0;
            }
            const uint32_t step0 = __shfl_sync(0xffffffffu, s_misc[M_STEP0 + wg], 0);
            const uint32_t T = (__shfl_sync(0xffffffffu, s_misc[M_STEP0 + 1 + wg], 0) - step0 + NSTEP - 1) / NSTEP;
            uint32_t dx = (1u << 16) | ((sb + SM_RING + wg * (2 * TB)) >> 4);
            uint32_t de = (1u << 16) | ((sb + SM_EXT) >> 4);
            uint32_t ma = sb + SM_END + wg * MAXT * 4;
            uint32_t gptr = opaque32(sb + SM_GI + wg * GPW * 64 + t4 * 16);
            auto pin = [&](uint32_t v) { return __shfl_sync(0xffffffffu, v + lane, lane) - lane; };
            const uint32_t tb4 = pin(ch * 4);
            uint32_t ro[2];
            const uint32_t turn = pin(1 + wg), next = pin(1 + ((wg + 1) & 3));
            uint32_t flags = 0;
#pragma unroll 1
            for (int row = GPW - 1; (row + 1) * NWG * 8 > nvalid; row--) {
                const int pos = (row * NWG + ((row & 1) ? NWG - 1 - wg : wg)) * 8 + 2 * t4;
                flags |= ((pos + 1 >= nvalid ? 1u : 0u) | (pos >= nvalid ? 0x10000u : 0u)) << (GPW - 1 - row);
            }
            uint32_t hN[2], hD[2], hA[2], u2[2], x2[2] = {0, 0}, zmax = 0;
            uint4 gi;
            uint2 t0, t1;
            auto fetch_group = [&]() {
                gi = lds128(gptr);
                gptr += 64;
                t0 = lds64(gi.x ^ tb4); t1 = lds64(gi.z ^ tb4);
            };
            auto next_a = [&]() {
                const uint32_t a0 = __byte_perm(t0.x, t1.x, 0x5410), a1 = __byte_perm(t0.x, t1.x, 0x7632);
                hA[0] = hsub2(a0, fe[2]); hA[1] = hsub2(a1, fe[3]);
                fe[2] = a0; fe[3] = a1;
            };
            auto next_rows = [&]() {
                ro[0] = gi.y + (tb4 >> 1); ro[1] = gi.w + (tb4 >> 1);
                u2[0] = __byte_perm(t0.y, t1.y, 0x5410); u2[1] = __byte_perm(t0.y, t1.y, 0x7632);
            };
            auto flush_group = [&](const uint32_t (&hN)[2], const uint32_t (&hD)[2]) {
                uint32_t z[2];
#pragma unroll
                for (int r = 0; r < 2; r++) {
                    const float d0 = h_lo(hD[r]), d1 = h_hi(hD[r]);
                    const float rr = rcp(d0 * d1);
                    uint32_t r2;
                    asm("cvt.rn.satfinite.f16x2.f32 %0, %1, %2;" : "=r"(r2) : "f"(rr * d0), "f"(rr * d1));
                    z[r] = hfma2(hN[r], r2, u2[r]);
                }
                const uint32_t o0 = finish2(h_lo(z[0]), h_lo(z[1]), x2[0]), o1 = finish2(h_hi(z[0]), h_hi(z[1]), x2[1]);
                asm volatile("st.global.u32 [%0], %1;" ::"l"(reinterpret_cast<char*>(p.out) + ro[0]), "r"(o0) : "memory");
                asm volatile("st.global.u32 [%0], %1;" ::"l"(reinterpret_cast<char*>(p.out) + ro[1]), "r"(o1) : "memory");
                zmax = hamax2(zmax, hamax2(z[0], z[1]));
                flags = __funnelshift_r(flags, flags, 1) ^ (~(__vminu2(hD[0], hD[1]) + (0x80008000u - DEN_SMALL)) & 0x80008000u);
            };
            auto gate = [&](uint32_t g) { return pack_h(1.f + tanh_(h_lo(g)), 1.f + tanh_(h_hi(g))); };
            uint32_t db[2 * NSTEP], dv[2 * NSTEP];
            fetch_group();
            next_a();
            next_rows();
            hN[0] = hN[1] = 0; hD[0] = hD[1] = DEN0;
            if (wg == NWG - 1) bar_arrive<1, 288>();
            const uint32_t mend = ma + 4 * T;
#pragma unroll 1
            while (ma != mend) {
                uint32_t m;
                asm volatile("ld.shared.u32 %0, [%1];" : "=r"(m) : "r"(ma));
                ma += 4;
                bar_sync<288>(turn);
                wg_fence();
                mma_rs<0, 0>(dv, fv, dx);
                mma_rs<0, 0>(db, fb, dx);
#pragma unroll
                for (int k = 1; k < 4; k++) {
                    mma_rs<1, 0>(dv, fv + 4 * k, dx + 2 * k);
                    mma_rs<1, 0>(db, fb + 4 * k, dx + 2 * k);
                }
                mma_rs<1, 1>(db, fe, de);
                wg_commit();
                dx ^= TB >> 4;
                de ^= 128;
                auto block = [&](int e) {
                    bar_arrive<288>(next);
                    if (e > 0) {
                        asm volatile("ld.global.nc.u32 %0, [%1];" : "=r"(x2[0]) : "l"(reinterpret_cast<const char*>(p.x) + ro[0]));
                        asm volatile("ld.global.nc.u32 %0, [%1];" : "=r"(x2[1]) : "l"(reinterpret_cast<const char*>(p.x) + ro[1]));
                        fetch_group();
                    }
                    wg_wait();
                    keep(dv); keep(db); keep(fe);
                    if (e > 0) next_a();
                    uint32_t oN[2], oD[2];
#pragma unroll
                    for (int j = 0; j < NSTEP; j++) {
#pragma unroll
                        for (int r = 0; r < 2; r++) {
                            const uint32_t w = gate(e > 0 && j >= e ? hadd2(db[2 * j + r], hA[r]) : db[2 * j + r]);
                            hN[r] = hfma2(w, dv[2 * j + r], hN[r]);
                            hD[r] = hadd2(w, hD[r]);
                        }
                        if (j + 1 == e) {
                            oN[0] = hN[0]; oN[1] = hN[1]; oD[0] = hD[0]; oD[1] = hD[1];
                            hN[0] = hN[1] = 0; hD[0] = hD[1] = DEN0;
                        }
                    }
                    if (e > 0) { flush_group(oN, oD); next_rows(); }
                };
                if (m == 0) block(0);
                else if (m > 4) { if (m > 6) { if (m > 7) block(8); else block(7); } else { if (m > 5) block(6); else block(5); } }
                else { if (m > 2) { if (m > 3) block(4); else block(3); } else { if (m > 1) block(2); else block(1); } }
            }
            for (uint32_t i = T, n = max_tiles(); i < n; i++) {
                bar_sync<288>(turn);
                bar_arrive<288>(next);
            }
            if (wg == 0) bar_sync<1, 288>();
            if (__any_sync(0xffffffffu, flags != 0)) redo_small(p.x, p.wb, p.wv, p.wc, p.out, flags, wg, node0);
            asm volatile("{\n.reg .pred q;\nsetp.ge.u32 q, %1, 0x7c00;\nbar.red.or.pred q, %2, %3, q;\nselp.u32 %0, 1, 0, q;\n}"
                         : "=r"(plain) : "r"(hmag(zmax) | s_misc[M_LATE] << 15), "n"((int)B_FINAL), "n"(NT) : "memory");
        }
        if (plain) slow_bin(p, sm, node0, nvalid);
    }
}

typedef CUresult (*EncodeFn)(CUtensorMap*, CUtensorMapDataType, cuuint32_t, void*, const cuuint64_t*, const cuuint64_t*,
                             const cuuint32_t*, const cuuint32_t*, CUtensorMapInterleave, CUtensorMapSwizzle,
                             CUtensorMapL2promotion, CUtensorMapFloatOOBfill);

}

extern "C" void kernel_launch(void* const* d_in, const int* in_sizes, int n_in, void* d_out, int out_size) {
    static int sms = 0;
    static EncodeFn encode = nullptr;
    static void *cell = nullptr, *ext = nullptr, *cnt = nullptr, *x16 = nullptr, *len = nullptr;
    if (!sms) {
        int dev = 0;
        cudaGetDevice(&dev);
        cudaDeviceGetAttribute(&sms, cudaDevAttrMultiProcessorCount, dev);
        cudaFuncSetAttribute(gatedgcn_kernel<1>, cudaFuncAttributeMaxDynamicSharedMemorySize, SM_TOTAL);
        cudaFuncSetAttribute(gatedgcn_kernel<2>, cudaFuncAttributeMaxDynamicSharedMemorySize, SM_TOTAL);
        cudaFuncSetAttribute(gatedgcn_kernel<3>, cudaFuncAttributeMaxDynamicSharedMemorySize, SM_TOTAL);
        cudaDriverEntryPointQueryResult qr;
        cudaGetDriverEntryPoint("cuTensorMapEncodeTiled", (void**)&encode, cudaEnableDefault, &qr);
        cudaGetSymbolAddress(&cell, g_cell);
        cudaGetSymbolAddress(&ext, g_ext);
        cudaGetSymbolAddress(&cnt, g_cnt);
        cudaGetSymbolAddress(&len, g_len);
        cudaGetSymbolAddress(&x16, g_x16);
        if (((uint64_t)x16 >> 32) != (((uint64_t)x16 + G * NSLOT * 128 - 1) >> 32)) x16 = (char*)x16 + G * NSLOT * 128;
    }
    Params p;
    p.x = (const __nv_bfloat16*)d_in[0];
    p.e = (const __nv_bfloat16*)d_in[1];
    p.src = (const int*)d_in[2];
    p.dst = (const int*)d_in[3];
    p.wa = (const __nv_bfloat16*)d_in[4];
    p.wb = (const __nv_bfloat16*)d_in[5];
    p.wc = (const __nv_bfloat16*)d_in[6];
    p.wu = (const __nv_bfloat16*)d_in[7];
    p.wv = (const __nv_bfloat16*)d_in[8];
    p.out = (__nv_bfloat16*)d_out;
    p.cell = (uint4*)cell;
    p.ext = (uint64_t*)ext;
    p.len = (uint32_t*)len;
    p.cnt = (uint32_t*)cnt;
    p.x16 = (const uint4*)x16;
    p.N = in_sizes[0] / 64;
    p.E = in_sizes[2];
    p.npc = (p.N + G - 1) / G;
    p.chunk = ((p.E + G - 1) / G + 7) & ~7;
    p.magic = (uint32_t)(0x100000000ull / (uint32_t)p.npc) + 1u;
    if (!encode || p.npc > NROW || p.N - (G - 1) * p.npc < 8 * NWG || p.chunk > CHUNK_MAX || (p.E & 7) ||
        p.E - (G - 1) * p.chunk <= (NWG - 1) * VWG * 4) return;

    CUtensorMap xmap, hmap;
    const cuuint64_t dims[2] = {64, (cuuint64_t)p.N};
    const cuuint64_t strides[1] = {128};
    const cuuint32_t box[2] = {64, XROWS}, estr[2] = {1, 1};
    encode(&xmap, CU_TENSOR_MAP_DATA_TYPE_BFLOAT16, 2, d_in[0], dims, strides, box, estr, CU_TENSOR_MAP_INTERLEAVE_NONE,
           CU_TENSOR_MAP_SWIZZLE_128B, CU_TENSOR_MAP_L2_PROMOTION_L2_256B, CU_TENSOR_MAP_FLOAT_OOB_FILL_NONE);
    encode(&hmap, CU_TENSOR_MAP_DATA_TYPE_FLOAT16, 2, x16, dims, strides, box, estr, CU_TENSOR_MAP_INTERLEAVE_NONE,
           CU_TENSOR_MAP_SWIZZLE_128B, CU_TENSOR_MAP_L2_PROMOTION_NONE, CU_TENSOR_MAP_FLOAT_OOB_FILL_NONE);
    if (sms >= G) {
        gatedgcn_kernel<3><<<G, NTA, SM_TOTAL>>>(p, xmap, hmap);
    } else {
        gatedgcn_kernel<1><<<G, NTA, SM_TOTAL>>>(p, xmap, hmap);
        gatedgcn_kernel<2><<<G, NTA, SM_TOTAL>>>(p, xmap, hmap);
    }
}
```

```cpp
#include <cuda_runtime.h>
#include <cuda_bf16.h>
#include <cuda_fp16.h>
#include <cuda.h>
#include <stdint.h>

namespace {

constexpr int G = 132;
constexpr int NWG = 4;
constexpr int NT = NWG * 128;
constexpr int NW = NT / 32;
constexpr int NTA = NT + 128;
constexpr int NSLOT = 384;
constexpr int NROW = 380;
constexpr int GPW = NSLOT / 8 / NWG;
constexpr int XROWS = NSLOT / NWG;
constexpr int VPT = 3;
constexpr int VWG = 128 * VPT;
constexpr int CHUNK_MAX = NT * VPT * 4;
constexpr int CV = 18;
constexpr int CX = 36;
constexpr int CAPC = 3 * CV + CX;
constexpr int LSTR = 160;
constexpr int BPR = NT / CV;
constexpr int RND = (G + BPR - 1) / BPR;
constexpr int RNC = (G * CV + NT - 1) / NT;
constexpr int TPL = 4;
constexpr int NSTEP = 8;
constexpr int TB = NSTEP * 8 * 128;
constexpr int CAP = 6784;
constexpr int CAPX = CAP + NSTEP * 8;
constexpr int MAXT = 40;
static_assert(GPW % 2 == 0 && GPW <= 16 && G % 3 == 0 && G <= 192 && RNC == 5, "layout");

constexpr uint32_t SB = 1024;
constexpr int SM_RING = 0;
constexpr int SM_W = SM_RING + NSLOT * 128;
constexpr int SM_TBL = SM_W + 4 * 8192;
constexpr int SM_ENT = SM_TBL + NROW * 256;
constexpr int SM_EXT = SM_ENT + CHUNK_MAX * 6;
constexpr int SM_DEG = SM_EXT + 4096;
constexpr int SM_DH = SM_DEG + 512 * 4;
constexpr int SM_LG = SM_DH + 64 * 4;
constexpr int SM_END = SM_LG + 64 * 4;
constexpr int SM_MISC = SM_END + NWG * MAXT * 4;
constexpr int SM_HIST = SM_MISC + 64;
constexpr int SM_CUR = SM_HIST + 144 * 4;
constexpr int SM_GI = SM_CUR + 512 * 4;
constexpr int SM_BAR = SM_GI + (NWG * GPW + 1) * 64;
constexpr int SM_LBAR = SM_BAR + 96;
constexpr int SM_WC = SM_LBAR + 32;
constexpr int SM_TOTAL = SM_WC + 128;
constexpr int LND = 2 * NT * 16;
constexpr int SM_LND2 = SM_TBL + (NWG - 1) * XROWS * 256;
static_assert(SM_TOTAL <= 232448 && NSLOT * 128 * 4 <= SM_DEG, "smem");
static_assert(NWG * 2 * TB <= SM_W + 16384 && SM_TBL % 1024 == 0 && SM_EXT % 1024 == 0 && (SB + SM_EXT) % 4096 < 2048, "align");
static_assert((G + 1) * CAPC * 8 <= NROW * 256 && CAPC % 2 == 0, "outgoing cells");
static_assert(CAPX * 4 <= CHUNK_MAX * 6 && 2 * LND <= CHUNK_MAX * 6 && SM_LND2 + G * CV * 16 - 2 * LND <= SM_ENT, "aliases");
static_assert(SM_CUR % 16 == 0 && SM_GI % 16 == 0 && SM_WC % 16 == 0, "vector access");
enum { M_NOFIT, M_LATE, M_XBIG, M_XBAD, M_RANGE, M_SKIP, M_EPOCH, M_STEP0 = 8 };
enum { B_EDGE = 6, B_NODE, B_SENT, B_FINAL, B_CONV, B_COUNT, B_READY, B_SORT, B_GO, B_ROWS };

__device__ __align__(128) uint4 g_cell[G * G * CV];
__device__ __align__(128) uint64_t g_ext[G * G * CX];
__device__ __align__(128) uint32_t g_len[G * LSTR];
__device__ __align__(128) uint4 g_x16[2 * G * NSLOT * 8];
__device__ __align__(128) uint32_t g_cnt[64];

constexpr uint32_t DEN0 = 0x00220022u;
constexpr uint32_t DEN_SMALL = 0x03470347u;
constexpr uint32_t E_PAD = 0xffff0000u;
constexpr uint32_t H_MAX = 0x4ff0u;
constexpr uint32_t A_MAX = 0x5000u;
constexpr uint32_t SQ_MAX = 0x6380u;
constexpr uint32_t SQ_MIN = 0x2240u;

__device__ __forceinline__ float tanh_(float x) { float y; asm("tanh.approx.f32 %0, %1;" : "=f"(y) : "f"(x)); return y; }
__device__ __forceinline__ float rcp(float x) { float y; asm("rcp.approx.ftz.f32 %0, %1;" : "=f"(y) : "f"(x)); return y; }
__device__ __forceinline__ uint32_t pack_bf16(float lo, float hi) { uint32_t r; asm("cvt.rn.bf16x2.f32 %0, %1, %2;" : "=r"(r) : "f"(hi), "f"(lo)); return r; }
__device__ __forceinline__ uint32_t pack_h(float lo, float hi) { uint32_t r; asm("cvt.rn.f16x2.f32 %0, %1, %2;" : "=r"(r) : "f"(hi), "f"(lo)); return r; }
__device__ __forceinline__ float h_lo(uint32_t v) { return __low2float(*reinterpret_cast<__half2*>(&v)); }
__device__ __forceinline__ float h_hi(uint32_t v) { return __high2float(*reinterpret_cast<__half2*>(&v)); }
__device__ __forceinline__ uint32_t hadd2(uint32_t a, uint32_t b) { uint32_t r; asm("add.rn.f16x2 %0, %1, %2;" : "=r"(r) : "r"(a), "r"(b)); return r; }
__device__ __forceinline__ uint32_t hsub2(uint32_t a, uint32_t b) { uint32_t r; asm("sub.rn.f16x2 %0, %1, %2;" : "=r"(r) : "r"(a), "r"(b)); return r; }
__device__ __forceinline__ uint32_t hfma2(uint32_t a, uint32_t b, uint32_t c) { uint32_t r; asm("fma.rn.f16x2 %0, %1, %2, %3;" : "=r"(r) : "r"(a), "r"(b), "r"(c)); return r; }
__device__ __forceinline__ uint32_t hamax2(uint32_t a, uint32_t b) { uint32_t r; asm("max.NaN.xorsign.abs.f16x2 %0, %1, %2;" : "=r"(r) : "r"(a), "r"(b)); return r; }
__device__ __forceinline__ uint32_t hmag(uint32_t m) { return max(m & 0x7fffu, (m >> 16) & 0x7fffu); }
__device__ __forceinline__ float bf_lo(uint32_t v) { return __uint_as_float(v << 16); }
__device__ __forceinline__ float bf_hi(uint32_t v) { return __uint_as_float(v & 0xffff0000u); }
__device__ __forceinline__ uint32_t bf2h(uint32_t v) { return pack_h(bf_lo(v), bf_hi(v)); }
__device__ __forceinline__ uint32_t finish2(float z0, float z1, uint32_t x) {
    uint32_t z, o;
    asm("cvt.rn.relu.bf16x2.f32 %0, %1, %2;" : "=r"(z) : "f"(z1), "f"(z0));
    asm("fma.rn.bf16x2 %0, %1, %2, %3;" : "=r"(o) : "r"(z), "r"(0x3b803b80u), "r"(x));
    return o;
}
__device__ __forceinline__ uint32_t opaque32(uint32_t v) { asm volatile("" : "+r"(v)); return v; }
__device__ __forceinline__ uint2 lds64(uint32_t a) { uint2 v; asm volatile("ld.shared.v2.u32 {%0,%1}, [%2];" : "=r"(v.x), "=r"(v.y) : "r"(a)); return v; }
__device__ __forceinline__ uint4 lds128(uint32_t a) {
    uint4 v;
    asm("ld.shared.v4.u32 {%0,%1,%2,%3}, [%4];" : "=r"(v.x), "=r"(v.y), "=r"(v.z), "=r"(v.w) : "r"(a));
    return v;
}

__device__ __forceinline__ void spin_limit(uint32_t it) {
    asm volatile("{\n.reg .pred q;\n.reg .b64 z;\nmov.b64 z, 0;\nsetp.gt.u32 q, %0, 0x400000;\n@q st.global.u32 [z], %0;\n}" ::"r"(it));
}
__device__ __forceinline__ void wg_fence() { asm volatile("wgmma.fence.sync.aligned;" ::: "memory"); }
__device__ __forceinline__ void wg_commit() { asm volatile("wgmma.commit_group.sync.aligned;" ::: "memory"); }
__device__ __forceinline__ void wg_wait() { asm volatile("wgmma.wait_group.sync.aligned 0;" ::: "memory"); }
__device__ __forceinline__ void proxy_fence() { asm volatile("fence.proxy.async.shared::cta;" ::: "memory"); }
__device__ __forceinline__ void cp_commit() { asm volatile("cp.async.commit_group;" ::: "memory"); }
__device__ __forceinline__ void cp_wait() { asm volatile("cp.async.wait_group 0;" ::: "memory"); }
__device__ __forceinline__ void cp16(uint32_t dst, const void* src) { asm volatile("cp.async.cg.shared.global [%0], [%1], 16;" ::"r"(dst), "l"(src) : "memory"); }
template <int ID, int N> __device__ __forceinline__ void bar_sync() { asm volatile("bar.sync %0, %1;" ::"n"(ID), "n"(N) : "memory"); }
template <int ID, int N> __device__ __forceinline__ void bar_arrive() { asm volatile("bar.arrive %0, %1;" ::"n"(ID), "n"(N) : "memory"); }
template <int N> __device__ __forceinline__ void bar_sync(uint32_t id) { asm volatile("bar.sync %0, %1;" ::"r"(id), "n"(N) : "memory"); }
template <int N> __device__ __forceinline__ void bar_arrive(uint32_t id) { asm volatile("bar.arrive %0, %1;" ::"r"(id), "n"(N) : "memory"); }
__device__ __forceinline__ uint32_t ld_relaxed(const uint32_t* p) {
    uint32_t v;
    asm volatile("ld.relaxed.gpu.global.u32 %0, [%1];" : "=r"(v) : "l"(p) : "memory");
    return v;
}
__device__ __forceinline__ void st_relaxed(uint32_t* p, uint32_t v) { asm volatile("st.relaxed.gpu.global.u32 [%0], %1;" ::"l"(p), "r"(v) : "memory"); }
__device__ __forceinline__ uint2 ld_relaxed8(const void* p) {
    uint2 v;
    asm volatile("{\n.reg .b64 t;\nld.relaxed.gpu.global.b64 t, [%2];\nmov.b64 {%0, %1}, t;\n}" : "=r"(v.x), "=r"(v.y) : "l"(p) : "memory");
    return v;
}
__device__ __forceinline__ void st_relaxed8(void* p, uint32_t lo, uint32_t hi) {
    asm volatile("{\n.reg .b64 t;\nmov.b64 t, {%1, %2};\nst.relaxed.gpu.global.b64 [%0], t;\n}" ::"l"(p), "r"(lo), "r"(hi) : "memory");
}
__device__ __forceinline__ void bulk_load(uint32_t dst, const void* src, uint32_t bytes, uint32_t bar) {
    asm volatile("cp.async.bulk.shared::cluster.global.mbarrier::complete_tx::bytes [%0], [%1], %2, [%3];"
                 ::"r"(dst), "l"(src), "r"(bytes), "r"(bar) : "memory");
}
__device__ __forceinline__ void mbar_init(uint32_t bar) { asm volatile("mbarrier.init.shared::cta.b64 [%0], 1;" ::"r"(bar) : "memory"); }
__device__ __forceinline__ void expect_tx(uint32_t bar, uint32_t bytes) {
    asm volatile("mbarrier.arrive.expect_tx.shared::cta.b64 _, [%0], %1;" ::"r"(bar), "r"(bytes) : "memory");
}
__device__ __forceinline__ bool mbar_try(uint32_t bar) {
    uint32_t ok;
    asm volatile("{\n.reg .pred q;\nmbarrier.try_wait.parity.shared::cta.b64 q, [%1], 0;\nselp.u32 %0, 1, 0, q;\n}"
                 : "=r"(ok) : "r"(bar) : "memory");
    return ok;
}
__device__ __forceinline__ void mbar_wait(uint32_t bar) {
    for (uint32_t it = 0; !mbar_try(bar); it++) spin_limit(it);
}
__device__ __forceinline__ void ld_relaxed16_if(uint4& v, const uint4* p, bool on) {
    asm volatile("{\n.reg .pred q;\n.reg .b128 t;\n.reg .b64 a, b;\nsetp.ne.u32 q, %5, 0;\n"
                 "mov.b64 a, {%0, %1};\nmov.b64 b, {%2, %3};\nmov.b128 t, {a, b};\n@q ld.relaxed.gpu.global.b128 t, [%4];\n"
                 "mov.b128 {a, b}, t;\nmov.b64 {%0, %1}, a;\nmov.b64 {%2, %3}, b;\n}"
                 : "+r"(v.x), "+r"(v.y), "+r"(v.z), "+r"(v.w) : "l"(p), "r"((uint32_t)on) : "memory");
}
__device__ __forceinline__ void st_relaxed16(uint4* p, uint4 v) {
    asm volatile("{\n.reg .b128 t;\n.reg .b64 a, b;\nmov.b64 a, {%1, %2};\nmov.b64 b, {%3, %4};\nmov.b128 t, {a, b};\n"
                 "st.relaxed.gpu.global.b128 [%0], t;\n}"
                 ::"l"(p), "r"(v.x), "r"(v.y), "r"(v.z), "r"(v.w) : "memory");
}

#define R4(d, o) "+r"(d[o]), "+r"(d[o + 1]), "+r"(d[o + 2]), "+r"(d[o + 3])
#define L16 "%0,%1,%2,%3,%4,%5,%6,%7,%8,%9,%10,%11,%12,%13,%14,%15"
#define L24 L16 ",%16,%17,%18,%19,%20,%21,%22,%23"
constexpr uint32_t HI_SW = 0x40000000u | 64u;
template <int A>
__device__ __forceinline__ void mma_ss(uint32_t (&d)[24], uint32_t alo, uint32_t blo) {
    asm volatile("{\n.reg .b64 a, b;\nmov.b64 a, {%24, %26};\nmov.b64 b, {%25, %26};\n"
                 "wgmma.mma_async.sync.aligned.m64n96k16.f16.f16.f16 {" L24 "}, a, b, %27, 1, 1, 1, 0;\n}\n"
                 : R4(d, 0), R4(d, 4), R4(d, 8), R4(d, 12), R4(d, 16), R4(d, 20)
                 : "r"(alo), "r"(blo), "r"(HI_SW), "n"(A));
}
template <int A, int T>
__device__ __forceinline__ void mma_rs(uint32_t (&d)[16], const uint32_t* a, uint32_t blo) {
    asm volatile("{\n.reg .b64 b;\nmov.b64 b, {%20, %21};\n"
                 "wgmma.mma_async.sync.aligned.m64n64k16.f16.f16.f16 {" L16 "}, {%16,%17,%18,%19}, b, %22, 1, 1, %23;\n}\n"
                 : R4(d, 0), R4(d, 4), R4(d, 8), R4(d, 12)
                 : "r"(a[0]), "r"(a[1]), "r"(a[2]), "r"(a[3]), "r"(blo), "r"(HI_SW), "n"(A), "n"(T));
}
template <int R> __device__ __forceinline__ void keep(uint32_t (&d)[R]) {
#pragma unroll
    for (int i = 0; i < R; i++) asm volatile("" : "+r"(d[i])::"memory");
}
__device__ __forceinline__ void ldsm_t(uint32_t* f, uint32_t addr) {
    asm volatile("ldmatrix.sync.aligned.m8n8.x4.trans.shared.b16 {%0,%1,%2,%3}, [%4];"
                 : "=r"(f[0]), "=r"(f[1]), "=r"(f[2]), "=r"(f[3]) : "r"(addr) : "memory");
}
__device__ __forceinline__ uint32_t stage_w(unsigned char* mat, int k, int c, uint4 a, uint4 b, float s) {
    unsigned char* row = mat + k * 128;
    const uint4 e = make_uint4(pack_h(s * bf_lo(a.x), s * bf_lo(a.y)), pack_h(s * bf_lo(a.z), s * bf_lo(a.w)),
                               pack_h(s * bf_lo(b.x), s * bf_lo(b.y)), pack_h(s * bf_lo(b.z), s * bf_lo(b.w)));
    const uint4 o = make_uint4(pack_h(s * bf_hi(a.x), s * bf_hi(a.y)), pack_h(s * bf_hi(a.z), s * bf_hi(a.w)),
                               pack_h(s * bf_hi(b.x), s * bf_hi(b.y)), pack_h(s * bf_hi(b.z), s * bf_hi(b.w)));
    *reinterpret_cast<uint4*>(row + ((c ^ (k & 7)) << 4)) = e;
    *reinterpret_cast<uint4*>(row + (((c + 1) ^ (k & 7)) << 4)) = o;
    return hamax2(hamax2(hamax2(e.x, e.y), hamax2(e.z, e.w)), hamax2(hamax2(o.x, o.y), hamax2(o.z, o.w)));
}

struct Params {
    const int* dst;
    const int* src;
    const __nv_bfloat16* e;
    int N, E, npc, chunk;
    const __nv_bfloat16* x;
    __nv_bfloat16* out;
    uint32_t* cnt;
    const __nv_bfloat16 *wa, *wb, *wc, *wu, *wv;
    uint4* cell;
    uint64_t* ext;
    uint32_t* len;
    const uint4* x16;
    uint32_t magic;
};

__device__ __noinline__ void slow_bin(const Params& p, unsigned char* sm, int node0, int nvalid) {
    float* acc = reinterpret_cast<float*>(sm);
    const int tid = threadIdx.x, lane = tid & 31, warp = tid >> 5;
    bar_sync<B_EDGE, NT>();
    for (int i = tid; i < NSLOT * 128; i += NT) acc[i] = 0.f;
    bar_sync<B_EDGE, NT>();
    const uint32_t* x2 = reinterpret_cast<const uint32_t*>(p.x);
    const uint32_t* wb = reinterpret_cast<const uint32_t*>(p.wb) + lane;
    const uint32_t* wv = reinterpret_cast<const uint32_t*>(p.wv) + lane;
    const uint32_t* wa = reinterpret_cast<const uint32_t*>(p.wa) + lane;
    const uint32_t* wu = reinterpret_cast<const uint32_t*>(p.wu) + lane;
    const uint32_t wc = reinterpret_cast<const uint32_t*>(p.wc)[lane];
    for (int i0 = warp * 32; i0 < p.E; i0 += NT) {
        const int dl = i0 + lane < p.E ? p.dst[i0 + lane] - node0 : -1;
        uint32_t m = __ballot_sync(0xffffffffu, (uint32_t)dl < (uint32_t)nvalid);
        while (m) {
            const int l = __ffs(m) - 1;
            m &= m - 1;
            const int d = __shfl_sync(0xffffffffu, dl, l);
            const uint32_t xs = x2[p.src[i0 + l] * 32 + lane], xd = x2[(node0 + d) * 32 + lane];
            float g0 = 0.f, g1 = 0.f, v0 = 0.f, v1 = 0.f;
#pragma unroll 4
            for (int k = 0; k < 32; k++) {
                const uint32_t a = __shfl_sync(0xffffffffu, xs, k), b = __shfl_sync(0xffffffffu, xd, k);
#pragma unroll
                for (int h = 0; h < 2; h++) {
                    const float fs = h ? bf_hi(a) : bf_lo(a), fd = h ? bf_hi(b) : bf_lo(b);
                    const uint32_t ua = wa[(2 * k + h) * 32], ub = wb[(2 * k + h) * 32], uv = wv[(2 * k + h) * 32];
                    g0 += fd * bf_lo(ua) + fs * bf_lo(ub);
                    g1 += fd * bf_hi(ua) + fs * bf_hi(ub);
                    v0 += fs * bf_lo(uv);
                    v1 += fs * bf_hi(uv);
                }
            }
            const float ev = __bfloat162float(p.e[i0 + l]);
            const float e0 = rcp(1.f + __expf(-(g0 + ev * bf_lo(wc))));
            const float e1 = rcp(1.f + __expf(-(g1 + ev * bf_hi(wc))));
            float* a = acc + d * 128 + 2 * lane;
            atomicAdd(a, e0);
            atomicAdd(a + 1, e1);
            atomicAdd(a + 64, e0 * v0);
            atomicAdd(a + 65, e1 * v1);
        }
    }
    bar_sync<B_EDGE, NT>();
    for (int n = warp; n < nvalid; n += NW) {
        const uint32_t xd = x2[(node0 + n) * 32 + lane];
        float u0 = 0.f, u1 = 0.f;
#pragma unroll 4
        for (int k = 0; k < 32; k++) {
            const uint32_t b = __shfl_sync(0xffffffffu, xd, k);
            const uint32_t w0 = wu[(2 * k) * 32], w1 = wu[(2 * k + 1) * 32];
            u0 += bf_lo(b) * bf_lo(w0) + bf_hi(b) * bf_lo(w1);
            u1 += bf_lo(b) * bf_hi(w0) + bf_hi(b) * bf_hi(w1);
        }
        const float* a = acc + n * 128 + 2 * lane;
        const float z0 = u0 + a[64] * rcp(a[0] + 1e-6f), z1 = u1 + a[65] * rcp(a[1] + 1e-6f);
        const float r0 = z0 > 0.f ? z0 : 0.f * z0, r1 = z1 > 0.f ? z1 : 0.f * z1;
        reinterpret_cast<uint32_t*>(p.out)[(node0 + n) * 32 + lane] = pack_bf16(bf_lo(xd) + r0, bf_hi(xd) + r1);
    }
}

__device__ __noinline__ void redo_small(const void* px, const void* pwb, const void* pwv, const void* pwc, void* pout,
                                        uint32_t flags, int wg, int node0) {
    extern __shared__ __align__(1024) unsigned char sm[];
    const int lane = threadIdx.x & 31, g = lane >> 2, t = lane & 3;
    uint32_t i0 = 0;
    float den = 0.f, num = 0.f;
#pragma unroll 1
    for (uint32_t m; (m = __ballot_sync(0xffffffffu, flags != 0)) != 0;) {
        const int l = __ffs(m) - 1;
        const uint32_t k = __ffs(__shfl_sync(0xffffffffu, flags, l)) - 1;
        const uint32_t pr = ((threadIdx.x >> 5) & 3) * 8 + (l >> 2);
        const uint32_t ta = reinterpret_cast<const uint2*>(sm + SM_GI)[(wg * GPW + (k & 15) - (16 - GPW)) * 8 + 2 * (l & 3) + (k >> 4)].x;
        const uint32_t n = (ta - SB - SM_TBL) >> 8;
        const uint32_t deg = reinterpret_cast<const uint32_t*>(sm + SM_DEG)[n];
        const uint32_t base = (reinterpret_cast<const uint32_t*>(sm + SM_CUR)[n] >> 2) - 8 * deg;
        const uint2 tb = lds64(ta ^ (pr * 8));
        uint4 xr[4][2];
        uint32_t en[4], wr[16];
#pragma unroll
        for (int u = 0; u < 4; u++) {
            en[u] = reinterpret_cast<const uint32_t*>(sm + SM_ENT)[base + 8 * min(i0 + 8 * u + g, max(deg, 1u) - 1)];
            xr[u][0] = __ldg(reinterpret_cast<const uint4*>(px) + (en[u] & 0xffff) * 8 + 2 * t);
            xr[u][1] = __ldg(reinterpret_cast<const uint4*>(px) + (en[u] & 0xffff) * 8 + 2 * t + 1);
        }
        const uint16_t* w = reinterpret_cast<const uint16_t*>((g & 1) ? pwv : pwb) + 16 * t * 64 + 2 * pr + ((g >> 1) & 1);
#pragma unroll
        for (int i = 0; i < 16; i++) wr[i] = __ldg(w + i * 64);
        uint32_t x;
        asm volatile("ld.volatile.global.u32 %0, [%1];" : "=r"(x) : "l"(reinterpret_cast<const uint32_t*>(px) + (node0 + n) * 32 + pr));
        const float wc = bf_lo(__ldg(reinterpret_cast<const uint16_t*>(pwc) + 2 * pr + (t & 1)));
        const float a = 2.f * ((t & 1) ? h_hi(tb.x) : h_lo(tb.x));
#pragma unroll
        for (int u = 0; u < 4; u += 2) {
            float c[4] = {0.f, 0.f, 0.f, 0.f};
#pragma unroll
            for (int q = 0; q < 4; q++) {
                const uint4 r0 = xr[u][q >> 1], r1 = xr[u + 1][q >> 1];
                asm("mma.sync.aligned.m16n8k16.row.col.f32.bf16.bf16.f32 {%0,%1,%2,%3}, {%4,%5,%6,%7}, {%8,%9}, {%0,%1,%2,%3};"
                    : "+f"(c[0]), "+f"(c[1]), "+f"(c[2]), "+f"(c[3])
                    : "r"((q & 1) ? r0.z : r0.x), "r"((q & 1) ? r1.z : r1.x), "r"((q & 1) ? r0.w : r0.y), "r"((q & 1) ? r1.w : r1.y),
                      "r"(wr[4 * q] | wr[4 * q + 1] << 16), "r"(wr[4 * q + 2] | wr[4 * q + 3] << 16));
            }
#pragma unroll
            for (int h = 0; h < 2; h++) {
                float eta = rcp(1.f + __expf(-(a + c[2 * h] + h_hi(en[u + h]) * wc)));
                eta = i0 + 8 * (u + h) + g < deg ? eta : 0.f;
                den += eta;
                num += eta * c[2 * h + 1];
            }
        }
        i0 += 32;
        if (i0 >= deg) {
#pragma unroll
            for (int o = 4; o < 32; o <<= 1) { den += __shfl_xor_sync(0xffffffffu, den, o); num += __shfl_xor_sync(0xffffffffu, num, o); }
            const float agg = 256.f * num * rcp(den + 1e-6f);
            const uint32_t o = finish2(__shfl_sync(0xffffffffu, agg, 0) + h_lo(tb.y), __shfl_sync(0xffffffffu, agg, 1) + h_hi(tb.y), x);
            if (lane == l) {
                if (!(ta & 8)) reinterpret_cast<uint32_t*>(pout)[(node0 + n) * 32 + pr] = o;
                flags &= flags - 1;
            }
            i0 = 0; den = 0.f; num = 0.f;
        }
    }
}

template <int MODE>
__global__ void __launch_bounds__(NTA, 1) gatedgcn_kernel(const __grid_constant__ Params p, const __grid_constant__ CUtensorMap xmap,
                                                          const __grid_constant__ CUtensorMap hmap) {
    extern __shared__ __align__(1024) unsigned char sm[];
    constexpr uint32_t sb = SB;
    spin_limit((uint32_t)__cvta_generic_to_shared(sm) != SB ? ~0u : 0u);
    const int tid = threadIdx.x, lane = tid & 31;
    const int warp = __shfl_sync(0xffffffffu, tid >> 5, 0);
    const int wg = warp >> 2, w4 = warp & 3, g8 = lane >> 2, t4 = lane & 3, tw = tid & 127;
    const int cta = blockIdx.x;
    const int node0 = cta * p.npc;
    const int nvalid = min(p.npc, p.N - node0);
    const int ch = 16 * w4 + 2 * g8;
    const uint32_t share = cta == 0 ? 1024 - G + 1 : 1;

    uint32_t* s_hist = reinterpret_cast<uint32_t*>(sm + SM_HIST);
    uint32_t* s_deg = reinterpret_cast<uint32_t*>(sm + SM_DEG);
    uint32_t* s_cur = reinterpret_cast<uint32_t*>(sm + SM_CUR);
    uint2* s_gi = reinterpret_cast<uint2*>(sm + SM_GI);
    uint32_t* s_dh = reinterpret_cast<uint32_t*>(sm + SM_DH);
    uint32_t* s_lg = reinterpret_cast<uint32_t*>(sm + SM_LG);
    uint32_t* s_end = reinterpret_cast<uint32_t*>(sm + SM_END);
    uint32_t* s_misc = reinterpret_cast<uint32_t*>(sm + SM_MISC);
    uint32_t* s_ent = reinterpret_cast<uint32_t*>(sm + SM_ENT);
    auto max_tiles = [&]() {
        uint32_t tm = 0;
#pragma unroll
        for (int k = 0; k < NWG; k++) tm = max(tm, (s_misc[M_STEP0 + 1 + k] - s_misc[M_STEP0 + k] + NSTEP - 1) / NSTEP);
        return tm;
    };

    if (wg == NWG) {
        if (tw == 0) {
#pragma unroll
            for (int i = 0; i < 4; i++) mbar_init(sb + SM_LBAR + 8 * i);
            proxy_fence();
            if (MODE & 2) {
                expect_tx(sb + SM_LBAR + 24, 4 * 8192 + 128);
                bulk_load(sb + SM_W, p.wa, 8192, sb + SM_LBAR + 24);
                bulk_load(sb + SM_W + 8192, p.wu, 8192, sb + SM_LBAR + 24);
                bulk_load(sb + SM_W + 16384, p.wb, 8192, sb + SM_LBAR + 24);
                bulk_load(sb + SM_W + 24576, p.wv, 8192, sb + SM_LBAR + 24);
                bulk_load(sb + SM_WC, p.wc, 128, sb + SM_LBAR + 24);
            }
        }
        asm volatile("setmaxnreg.dec.sync.aligned.u32 32;");
        uint32_t mw = 0;
        if (MODE & 2) {
            {
                const int k = (tw >> 3) & 7;
                const uint32_t one = tw >= 64 ? 0x3c00u << (16 * (k & 1)) : 0u;
                const uint4 v = make_uint4(k >> 1 == 0 ? one : 0, k >> 1 == 1 ? one : 0, k >> 1 == 2 ? one : 0, k >> 1 == 3 ? one : 0);
                reinterpret_cast<uint4*>(sm + SM_EXT)[tw] = v;
                reinterpret_cast<uint4*>(sm + SM_EXT)[tw + 128] = v;
            }
            bar_sync<1 + NWG, 128>();
            mbar_wait(sb + SM_LBAR + 24);
            if (w4 == 0) {
                mw = reinterpret_cast<uint32_t*>(sm + SM_WC)[lane];
                mw = pack_h(0.5f * bf_lo(mw), 0.5f * bf_hi(mw));
                reinterpret_cast<uint32_t*>(sm + SM_WC)[lane] = mw;
                mw = hmag(mw);
            }
#pragma unroll 1
            for (int j = 0; j < 8; j++) {
                const uint4* w = reinterpret_cast<const uint4*>(sm + SM_W + j * 4096) + tw * 2;
                const uint4 a = w[0], b = w[1];
                __syncwarp();
                const uint32_t m = hmag(stage_w(sm + SM_W + j * 4096, tw >> 2, (tw & 3) * 2, a, b, (j & 2) ? 256.f : 0.5f));
                mw = max((int)mw, (int)m - ((j & 2) ? 8 << 10 : 0));
            }
        }
        proxy_fence();
        bar_sync<B_SENT, NTA>();
        const uint32_t epoch = s_misc[M_EPOCH];
        if (mw > H_MAX) s_misc[M_RANGE] = 1;
        if (w4 == 0) {
            if (MODE & 2) {
                if (MODE == 3 && lane == 0) for (uint32_t it = 0; ld_relaxed(p.cnt) != epoch << 10; it++) spin_limit(it);
                __syncwarp();
                bar_arrive<B_READY, 128>();
            }
            if ((MODE & 2) && lane == 0) {
                const uint4* in = p.cell + cta * G * CV;
                proxy_fence();
                expect_tx(sb + SM_LBAR, LND);
                bulk_load(sb + SM_ENT, in, LND, sb + SM_LBAR);
                expect_tx(sb + SM_LBAR + 8, LND);
                bulk_load(sb + SM_ENT + LND, in + LND / 16, LND, sb + SM_LBAR + 8);
                expect_tx(sb + SM_LBAR + 16, G * CV * 16 - 2 * LND);
                bulk_load(sb + SM_LND2, in + LND / 8, G * CV * 16 - 2 * LND, sb + SM_LBAR + 16);
            }
            if (MODE & 1) bar_sync<B_CONV, NT + 32>();
            if (MODE == 3) mbar_wait(sb + SM_LBAR + 8);
            if (lane == 0) {
                if (MODE & 1) {
#pragma unroll 1
                    for (int b = 0; b < NWG; b++)
                        asm volatile("cp.async.bulk.tensor.2d.global.shared::cta.bulk_group [%0, {%2, %3}], [%1];"
                                     ::"l"(&hmap), "r"(sb + SM_RING + b * XROWS * 128), "r"(0), "r"(node0 + b * XROWS) : "memory");
                    asm volatile("cp.async.bulk.commit_group;" ::: "memory");
                    if (s_misc[M_XBAD]) st_relaxed(p.cnt + 33, epoch);
                    asm volatile("cp.async.bulk.wait_group 0;" ::: "memory");
                    asm volatile("red.release.gpu.global.add.u32 [%0], %1;" ::"l"(p.cnt + 32), "r"(share) : "memory");
                }
                if (MODE & 2) {
                    uint2 c = ld_relaxed8(p.cnt + 32);
                    for (uint32_t it = 0; c.x != epoch << 10; it++) { c = ld_relaxed8(p.cnt + 32); spin_limit(it); }
                    asm volatile("fence.acquire.gpu;" ::: "memory");
                    if (c.y == epoch) s_misc[M_LATE] = 1;
                }
            }
            __syncwarp();
        } else if (MODE & 2) {
            const uint32_t tag23 = epoch << 9;
            const int t = tw - 32;
            const int c0 = (w4 - 1) * (G / 3);
            uint32_t ln[2] = {~tag23, lane < G / 3 - 32 ? ~tag23 : tag23};
            for (uint32_t it = 0; ((ln[0] ^ tag23) | (ln[1] ^ tag23)) > 0x1ff; it++) {
#pragma unroll
                for (int r = 0; r < 2; r++)
                    if ((ln[r] ^ tag23) > 0x1ff) ln[r] = ld_relaxed(p.len + cta * LSTR + c0 + lane + 32 * r);
                spin_limit(it);
            }
            __syncwarp();
            uint32_t at[TPL] = {}, nt = 0;
#pragma unroll
            for (int r = 0; r < 2; r++) {
                const uint32_t len = ln[r] & 0x1ff;
                if (len > CAPC) s_misc[M_NOFIT] = 1;
                for (uint32_t m = __ballot_sync(0xffffffffu, len > 3 * CV && len <= CAPC); m; m &= m - 1) {
                    const uint32_t l = __ffs(m) - 1;
#pragma unroll
                    for (int k = 0; k < TPL; k++)
                        if (lane + 32 * k >= nt) at[k] = (c0 + l + 32 * r) * CX + lane + 32 * k - nt;
                    nt += __reduce_max_sync(0xffffffffu, lane == l ? len : 0) - 3 * CV;
                }
            }
            if (nt > 32 * TPL) s_misc[M_NOFIT] = 1;
            uint2 v[TPL];
#pragma unroll
            for (int k = 0; k < TPL; k++) v[k] = make_uint2(0, lane + 32 * k < nt ? ~tag23 : tag23 | 511);
            bar_sync<B_READY, 128>();
            for (uint32_t it = 0; ((v[0].y ^ tag23) | (v[1].y ^ tag23) | (v[2].y ^ tag23) | (v[3].y ^ tag23)) > 0x1ff; it++) {
#pragma unroll
                for (int k = 0; k < TPL; k++)
                    if ((v[k].y ^ tag23) > 0x1ff) v[k] = ld_relaxed8(p.ext + cta * G * CX + at[k]);
                spin_limit(it);
            }
            __syncwarp();
#pragma unroll
            for (int k = 0; k < TPL; k++) atomicAdd(&s_deg[v[k].y & 0x1ff], 1u);
            bar_sync<B_COUNT, NT + 96>();
            const uint32_t pv = node0 | E_PAD;
            for (int k = t; k < CAPX / 4; k += 96) reinterpret_cast<uint4*>(s_ent)[k] = make_uint4(pv, pv, pv, pv);
            bar_sync<B_SORT, NT + 96>();
            if (s_misc[M_SKIP] == 0) {
#pragma unroll
                for (int k = 0; k < TPL; k++)
                    if (lane + 32 * k < nt) s_ent[atomicAdd(&s_cur[v[k].y & 0x1ff], 32u) >> 2] = v[k].x;
            }
        }
        if (!(MODE & 2)) return;
        if (w4 != 0) bar_sync<B_GO, NT + 96>(); else bar_sync<B_ROWS, 128>();
        if (s_misc[M_SKIP] | s_misc[M_RANGE] | (s_misc[M_XBIG] ^ 1)) {
            if (w4 != 0) bar_arrive<B_ROWS, 128>(); else bar_arrive<0, NT + 32>();
            return;
        }
        const int fw = (w4 + 3) & 3;
        const uint32_t step0 = s_misc[M_STEP0 + fw];
        const int T = (s_misc[M_STEP0 + 1 + fw] - step0 + NSTEP - 1) / NSTEP;
        const int q = lane >> 3, c8 = lane & 7;
        uint32_t sidx = sb + SM_ENT + step0 * 32 + q * 8;
        uint32_t sd0 = sb + SM_RING + fw * (2 * TB) + q * 256 + ((c8 ^ (2 * q)) << 4);
        uint32_t se = sb + SM_EXT + fw * 256 + ((c8 ^ (2 * fw)) << 4) + q * 4;
        const uint32_t xlo = (uint32_t)reinterpret_cast<uint64_t>(p.x16) + c8 * 16;
        const uint32_t xhi = (uint32_t)(reinterpret_cast<uint64_t>(p.x16) >> 32);
#pragma unroll 1
        for (int i = 0; i < T; i++) {
            uint2 nx[NSTEP];
            const uint2 ee = lds64(sidx + 32 * c8);
#pragma unroll
            for (int j = 0; j < NSTEP; j++) nx[j] = lds64(sidx + 32 * j);
            const uint32_t e2 = __byte_perm(ee.x, ee.y, 0x7632);
            uint32_t pm;
            asm("set.nan.u32.f16x2 %0, %1, %1;" : "=r"(pm) : "r"(e2));
            if (i > 0) {
                cp_wait();
                proxy_fence();
                bar_sync<288>(1 + fw);
            } else if (w4 != 0) {
                bar_sync<B_ROWS, 128>();
            }
            asm volatile("st.shared.u32 [%0], %1;" ::"r"(se), "r"(e2 & ~pm) : "memory");
            asm volatile("st.shared.u32 [%0+128], %1;" ::"r"(se ^ 16), "r"(pm & 0x40004000u) : "memory");
#pragma unroll
            for (int u = 0; u < 2 * NSTEP; u++) {
                uint64_t ga;
                asm("{\n.reg .b32 lo;\ndp2a.lo.u32.u32 lo, %1, 0x80, %2;\nmov.b64 %0, {lo, %3};\n}"
                    : "=l"(ga) : "r"((u & 1) ? nx[u >> 1].y : nx[u >> 1].x), "r"(xlo), "r"(xhi));
                cp16((sd0 ^ ((u & 1) * 16)) + (u & 1) * 128 + (u >> 1) * 1024, reinterpret_cast<const void*>(ga));
            }
            cp_commit();
            sidx += NSTEP * 32;
            sd0 ^= TB;
            se ^= 2048;
        }
        cp_wait();
        proxy_fence();
        for (uint32_t i = T - 1, n = max_tiles() + (fw == 0); i < n; i++) bar_sync<288>(1 + fw);
    } else {
        const uint32_t bar = sb + SM_BAR + wg * 24;
        const int e0 = cta * p.chunk + wg * VWG * 4;
        const int nvec = min(min(p.chunk - wg * VWG * 4, p.E - e0) >> 2, VWG);
        auto load_x = [&]() {
            if (tw == 0) {
                expect_tx(bar + 16, XROWS * 128);
                asm volatile("cp.async.bulk.tensor.2d.shared::cluster.global.mbarrier::complete_tx::bytes [%0], [%1, {%3, %4}], [%2];"
                             ::"r"(sb + SM_RING + wg * XROWS * 128), "l"(&xmap), "r"(bar + 16), "r"(0), "r"(node0 + wg * XROWS) : "memory");
            }
        };
        if (tw == 0) {
#pragma unroll
            for (int i = 0; i < 3; i++) mbar_init(bar + i * 8);
            proxy_fence();
            if (MODE & 1) {
                expect_tx(bar, nvec * 16);
                bulk_load(sb + SM_RING + wg * XROWS * 128, p.dst + e0, nvec * 16, bar);
            }
        }
        if (MODE == 2) load_x();
        const uint32_t cnt0 = ld_relaxed(p.cnt + opaque32(0));

        if (tid < (SM_CUR - SM_DEG) / 16) reinterpret_cast<uint4*>(sm + SM_DEG)[tid] = make_uint4(0, 0, 0, 0);
        if (tid < 32) s_cur[NSLOT + tid] = 0x80000000u;
        if (tid < 8) s_gi[NWG * GPW * 8 + tid] = make_uint2(sb + SM_TBL, 0);
        if (MODE & 1) {
#pragma unroll
            for (int j = 0; j < (G * CAPC / 2 + NT - 1) / NT; j++)
                if (tid + NT * j < G * CAPC / 2) reinterpret_cast<uint4*>(sm + SM_TBL)[tid + NT * j] = make_uint4(0, 511, 0, 511);
            if (tw == 0) {
                expect_tx(bar + 8, nvec * 24);
                bulk_load(sb + SM_ENT + wg * VWG * 24, p.src + e0, nvec * 16, bar + 8);
                bulk_load(sb + SM_ENT + wg * VWG * 24 + VWG * 16, p.e + e0, nvec * 8, bar + 8);
            }
        }
        bar_sync<B_EDGE, NT>();

        const uint32_t epoch = (cnt0 >> 10) + (MODE == 2 ? 0 : 1);
        const uint32_t tag5 = epoch << 27, tag23 = epoch << 9;
        if (MODE & 1) {
            int4 dv[VPT];
            mbar_wait(bar);
#pragma unroll
            for (int j = 0; j < VPT; j++) dv[j] = reinterpret_cast<const int4*>(sm + SM_RING + wg * XROWS * 128)[tw + 128 * j];
            uint32_t key[VPT * 4];
#pragma unroll
            for (int j = 0; j < VPT; j++) {
                const bool ok = tw + 128 * j < nvec;
                const int d[4] = {dv[j].x, dv[j].y, dv[j].z, dv[j].w};
#pragma unroll
                for (int q = 0; q < 4; q++) {
                    const uint32_t b = ok ? __umulhi((uint32_t)d[q], p.magic) : G;
                    const uint32_t r = atomicAdd(&s_hist[b], 1u);
                    key[j * 4 + q] = (b * CAPC + min(r, CAPC - 1u)) | ((uint32_t)(d[q] - b * p.npc) << 16);
                }
            }
            proxy_fence();
            bar_sync<B_EDGE, NT>();
            if (tid < G) st_relaxed(p.len + tid * LSTR + cta, min(s_hist[tid], 511u) | tag23);
            mbar_wait(bar + 8);
            load_x();
            uint2* stage = reinterpret_cast<uint2*>(sm + SM_TBL);
            uint32_t emax = 0;
#pragma unroll
            for (int j = 0; j < VPT; j++) {
                const uint4 sv = reinterpret_cast<const uint4*>(sm + SM_ENT + wg * VWG * 24)[tw + 128 * j];
                uint2 ev = reinterpret_cast<const uint2*>(sm + SM_ENT + wg * VWG * 24 + VWG * 16)[tw + 128 * j];
                ev.x = bf2h(ev.x); ev.y = bf2h(ev.y);
                if (tw + 128 * j < nvec) emax = hamax2(emax, hamax2(ev.x, ev.y));
                const uint32_t w0[4] = {__byte_perm(sv.x, ev.x, 0x5410), __byte_perm(sv.y, ev.x, 0x7610),
                                        __byte_perm(sv.z, ev.y, 0x5410), __byte_perm(sv.w, ev.y, 0x7610)};
#pragma unroll
                for (int q = 0; q < 4; q++) stage[key[j * 4 + q] & 0xffff] = make_uint2(w0[q], key[j * 4 + q] >> 16);
            }
            if (hmag(emax) > H_MAX) {
#pragma unroll
                for (int k = 0; k < VPT * 4; k++) stage[key[k] & 0xffff].y = 510;
            }
            bar_sync<B_EDGE, NT>();
            {
                const int b = warp + NW * lane;
                const uint32_t c = b < G ? s_hist[b] : 0;
                for (uint32_t m = __ballot_sync(0xffffffffu, c > 3 * CV); m; m &= m - 1) {
                    const int l = __ffs(m) - 1, bl = warp + NW * l;
                    const int n = min(__shfl_sync(0xffffffffu, c, l) - 3 * CV, CX);
#pragma unroll 1
                    for (int k = lane; (k & ~3) < n; k += 32) {
                        const uint2 v = stage[bl * CAPC + 3 * CV + k];
                        st_relaxed8(p.ext + (bl * G + cta) * CX + k, v.x, v.y | tag23);
                    }
                }
            }
            if (tid < BPR * CV) {
                const int xb = tid / CV, xi = tid - xb * CV;
                const uint2* st = stage + xb * CAPC + xi * 3;
                uint4* gc = p.cell + (xb * G + cta) * CV + xi;
                uint4 v[RND];
#pragma unroll
                for (int j = 0; j < RND; j++)
                    if (xb + BPR * j < G) {
                        const uint2 a = st[j * BPR * CAPC], b = st[j * BPR * CAPC + 1], c = st[j * BPR * CAPC + 2];
                        v[j] = make_uint4(a.x, b.x, c.x, a.y + b.y * 512 + c.y * 262144 + tag5);
                    }
#pragma unroll
                for (int j = 0; j < RND; j++)
                    if (xb + BPR * j < G) {
                        st_relaxed16(gc + j * BPR * G * CV, v[j]);
                        if (j == 2 && tid == NT - 32) asm volatile("red.relaxed.gpu.global.add.u32 [%0], %1;" ::"l"(p.cnt), "r"(share) : "memory");
                    }
            }
        }
        if (tid == 0) s_misc[M_EPOCH] = epoch;
        bar_sync<B_SENT, NTA>();
        asm volatile("setmaxnreg.inc.sync.aligned.u32 112;");
        {
            mbar_wait(bar + 16);
            uint4* xs = reinterpret_cast<uint4*>(sm + SM_RING + wg * XROWS * 128) + tw;
            uint4 v[XROWS / 16];
            uint32_t mx = 0, my = 0;
#pragma unroll
            for (int j = 0; j < XROWS / 16; j++) v[j] = xs[128 * j];
#pragma unroll
            for (int j = 0; j < XROWS / 16; j++) {
                v[j].x = bf2h(v[j].x); v[j].y = bf2h(v[j].y); v[j].z = bf2h(v[j].z); v[j].w = bf2h(v[j].w);
                xs[128 * j] = v[j];
                mx = hfma2(v[j].x, v[j].x, hfma2(v[j].z, v[j].z, mx));
                my = hfma2(v[j].y, v[j].y, hfma2(v[j].w, v[j].w, my));
            }
            if (hmag(hamax2(mx, my)) > SQ_MAX) s_misc[M_XBAD] = 1;
            if (hmag(hamax2(mx, my)) >= SQ_MIN) s_misc[M_XBIG] = 1;
            proxy_fence();
            if (MODE & 1) bar_arrive<B_CONV, NT + 32>();
            if (!(MODE & 2)) return;
            bar_sync<128>(1 + wg);
        }
        uint32_t da[24], du[24];
        {
            const uint32_t dx = (1u << 16) | ((sb + SM_RING + wg * XROWS * 128) >> 4);
            constexpr uint32_t dw = (1u << 16) | ((sb + SM_W) >> 4);
            wg_fence();
            mma_ss<0>(da, dw, dx);
            mma_ss<0>(du, dw + 512, dx);
#pragma unroll
            for (int k = 1; k < 4; k++) { mma_ss<1>(da, dw + 128 * k, dx + 2 * k); mma_ss<1>(du, dw + 512 + 128 * k, dx + 2 * k); }
            wg_commit();
            wg_wait();
            keep(da); keep(du);
        }
        auto table = [&]() {
            unsigned char* tb = sm + SM_TBL + (wg * XROWS + 2 * t4) * 256 + ((ch * 4) ^ (t4 << 5));
            uint32_t am = 0;
#pragma unroll
            for (int j = 0; j < 12; j++) {
                am = hamax2(am, hamax2(da[2 * j], da[2 * j + 1]));
#pragma unroll
                for (int h = 0; h < 2; h++)
                    if (j < 11 || wg * XROWS + 8 * j + 2 * t4 + h < NROW)
                        *reinterpret_cast<uint2*>(tb + (8 * j + h) * 256) =
                            make_uint2(__byte_perm(da[2 * j], da[2 * j + 1], h ? 0x7632 : 0x5410), __byte_perm(du[2 * j], du[2 * j + 1], h ? 0x7632 : 0x5410));
            }
            if (hmag(am) > A_MAX) s_misc[M_RANGE] = 1;
        };
        if (wg < NWG - 1) table();
        uint4 en[RNC];
        uint32_t d4[RNC * 3];
        auto count = [&](int j0, int j1) {
            mbar_wait(sb + SM_LBAR + 4 * j0);
#pragma unroll
            for (int j = j0; j < j1; j++) {
                if (j < RNC - 1 || tid + j * NT < G * CV) en[j] = reinterpret_cast<const uint4*>(sm + (j < 4 ? SM_ENT : SM_LND2 - 2 * LND))[j * NT + tid];
                else en[j] = make_uint4(0, 0, 0, tag5 | 0x7ffffffu);
            }
            for (uint32_t it = 0;; it++) {
                uint32_t miss = 0;
#pragma unroll
                for (int j = j0; j < j1; j++) miss |= en[j].w ^ tag5;
                if (miss < (1u << 27)) break;
#pragma unroll
                for (int j = j0; j < j1; j++)
                    ld_relaxed16_if(en[j], p.cell + cta * G * CV + tid + j * NT, (en[j].w ^ tag5) >= (1u << 27));
                spin_limit(it);
            }
            __syncwarp();
#pragma unroll
            for (int j = j0; j < j1; j++)
#pragma unroll
                for (int s = 0; s < 3; s++) {
                    d4[3 * j + s] = (s == 0 ? en[j].w << 2 : en[j].w >> (9 * s - 2)) & 0x7fc;
                    asm volatile("red.shared.add.u32 [%0+%1], 1;" ::"r"(d4[3 * j + s]), "n"(sb + SM_DEG) : "memory");
                }
        };
        count(0, 2);
        count(2, 4);
        count(4, RNC);
        bar_sync<B_COUNT, NT + 96>();
        uint32_t unused = 0;
        if (warp < NSLOT / 32) {
            const uint32_t dg = s_deg[tid];
            if (dg > 62 || s_deg[510]) s_misc[M_NOFIT] = 1;
            const uint32_t kb = tid < nvalid ? 62 - min(dg, 62u) : 63;
            const uint32_t r = atomicAdd(&s_dh[kb], 1u);
            bar_sync<B_NODE, NSLOT>();
            const uint2 h = reinterpret_cast<const uint2*>(s_dh)[lane];
            uint32_t inc = h.x + h.y;
#pragma unroll
            for (int o = 1; o < 32; o <<= 1) { const uint32_t v = __shfl_up_sync(0xffffffffu, inc, o); if (lane >= o) inc += v; }
            const uint32_t pe = __shfl_sync(0xffffffffu, inc - h.x - h.y, kb >> 1), po = __shfl_sync(0xffffffffu, inc - h.y, kb >> 1);
            const uint32_t pos = ((kb & 1) ? po : pe) + r;
            const uint32_t grp = pos >> 3, slot = pos & 7, row = grp / NWG, col = grp - row * NWG;
            const uint32_t seg = (row & 1) ? NWG - 1 - col : col;
            const uint32_t idx = seg * GPW + GPW - 1 - row;
            if (slot == 0) s_lg[idx] = max(dg, (uint32_t)NSTEP);
            bar_sync<B_NODE, NSLOT>();
            const uint2 l = reinterpret_cast<const uint2*>(s_lg)[lane];
            uint32_t in2 = l.x + l.y;
#pragma unroll
            for (int o = 1; o < 32; o <<= 1) { const uint32_t v = __shfl_up_sync(0xffffffffu, in2, o); if (lane >= o) in2 += v; }
            const uint32_t ex2 = in2 - l.x - l.y;
            const uint32_t mine = __shfl_sync(0xffffffffu, ex2, (lane / (GPW / 2)) * (GPW / 2));
            const uint32_t ee = __shfl_sync(0xffffffffu, in2 - l.y, idx >> 1), eo = __shfl_sync(0xffffffffu, in2, idx >> 1);
            const uint32_t sbeg = __shfl_sync(0xffffffffu, ex2, seg * (GPW / 2));
            if (__any_sync(0xffffffffu, in2 > CAP / 8 || in2 - mine > MAXT * NSTEP) || s_misc[M_NOFIT] != 0) {
                s_misc[M_SKIP] = 1;
            } else {
                const uint32_t gend = (idx & 1) ? eo : ee;
                s_cur[tid] = (gend - dg) * 32 + slot * 4;
                if (tid < nvalid) s_gi[idx * 8 + slot] = make_uint2(sb + SM_TBL + tid * 256 + (((tid >> 1) & 3) << 5), (node0 + tid) * 128);
                else unused = (idx * 8 + slot) | ((seg * GPW + GPW - 1) * 8 + slot) << 16;
                if (slot == 0) {
                    const uint32_t last = gend - 1 - sbeg;
                    s_end[seg * MAXT + last / NSTEP] = last % NSTEP + 1;
                }
                if (tid <= NWG * (GPW / 2) && tid % (GPW / 2) == 0) s_misc[M_STEP0 + tid / (GPW / 2)] = ex2;
            }
        } else {
            table();
        }
        bar_sync<B_SORT, NT + 96>();
        if (s_misc[M_SKIP] == 0) {
            if (unused) { const uint2 v = s_gi[unused >> 16]; s_gi[unused & 0xffff] = make_uint2(v.x ^ 8, v.y); }
            auto place = [&](int j1) {
#pragma unroll
                for (int k = 0; k < 3 * j1; k++)
                    asm volatile("atom.shared.add.u32 %0, [%1+%2], 32;" : "=r"(d4[k]) : "r"(min(d4[k], (NSLOT + lane) * 4u)), "n"(sb + SM_CUR) : "memory");
#pragma unroll
                for (int j = 0; j < j1; j++)
#pragma unroll
                    for (int s = 0; s < 3; s++)
                        asm volatile("{\n.reg .pred q;\nsetp.ge.s32 q, %0, 0;\n@q st.shared.u32 [%0+%2], %1;\n}"
                                     ::"r"(d4[3 * j + s]), "r"(s == 0 ? en[j].x : s == 1 ? en[j].y : en[j].z), "n"(sb + SM_ENT));
            };
            if (warp * 32 + (RNC - 1) * NT < G * CV) place(RNC); else place(RNC - 1);
        }
        bar_sync<B_GO, NT + 96>();
        uint32_t plain = s_misc[M_SKIP] | s_misc[M_RANGE] | (s_misc[M_XBIG] ^ 1);
        if (plain) {
            bar_sync<0, NT + 32>();
        } else {
            __nanosleep(wg * 120);
            uint32_t fb[16], fv[16], fe[4];
            {
                const uint32_t a = sb + SM_W + 16384 + ((lane >> 4) * 8 + (lane & 7)) * 128 + (((2 * w4 + ((lane >> 3) & 1)) ^ (lane & 7)) << 4);
#pragma unroll
                for (int k = 0; k < 4; k++) {
                    ldsm_t(fb + 4 * k, a + k * 2048);
                    ldsm_t(fv + 4 * k, a + 8192 + k * 2048);
                }
                const uint32_t wh = reinterpret_cast<const uint32_t*>(sm + SM_WC)[ch >> 1];
                fe[0] = t4 != wg ? 0 : __byte_perm(wh, 0xfb53, 0x5410);
                fe[1] = t4 != wg ? 0 : __byte_perm(wh, 0xfb53, 0x5432);
                fe[2] = fe[3] = 0;
            }
            const uint32_t step0 = __shfl_sync(0xffffffffu, s_misc[M_STEP0 + wg], 0);
            const uint32_t T = (__shfl_sync(0xffffffffu, s_misc[M_STEP0 + 1 + wg], 0) - step0 + NSTEP - 1) / NSTEP;
            uint32_t dx = (1u << 16) | ((sb + SM_RING + wg * (2 * TB)) >> 4);
            uint32_t de = (1u << 16) | ((sb + SM_EXT) >> 4);
            uint32_t ma = sb + SM_END + wg * MAXT * 4;
            uint32_t gptr = opaque32(sb + SM_GI + wg * GPW * 64 + t4 * 16);
            auto pin = [&](uint32_t v) { return __shfl_sync(0xffffffffu, v + lane, lane) - lane; };
            const uint32_t tb4 = pin(ch * 4);
            uint32_t ro[2];
            const uint32_t turn = pin(1 + wg), next = pin(1 + ((wg + 1) & 3));
            uint32_t flags = 0;
#pragma unroll 1
            for (int row = GPW - 1; (row + 1) * NWG * 8 > nvalid; row--) {
                const int pos = (row * NWG + ((row & 1) ? NWG - 1 - wg : wg)) * 8 + 2 * t4;
                flags |= ((pos + 1 >= nvalid ? 1u : 0u) | (pos >= nvalid ? 0x10000u : 0u)) << (GPW - 1 - row);
            }
            uint32_t hN[2], hD[2], hA[2], u2[2], x2[2] = {0, 0}, zmax = 0;
            uint4 gi;
            uint2 t0, t1;
            auto fetch_group = [&]() {
                gi = lds128(gptr);
                gptr += 64;
                t0 = lds64(gi.x ^ tb4); t1 = lds64(gi.z ^ tb4);
            };
            auto next_a = [&]() {
                const uint32_t a0 = __byte_perm(t0.x, t1.x, 0x5410), a1 = __byte_perm(t0.x, t1.x, 0x7632);
                hA[0] = hsub2(a0, fe[2]); hA[1] = hsub2(a1, fe[3]);
                fe[2] = a0; fe[3] = a1;
            };
            auto next_rows = [&]() {
                ro[0] = gi.y + (tb4 >> 1); ro[1] = gi.w + (tb4 >> 1);
                u2[0] = __byte_perm(t0.y, t1.y, 0x5410); u2[1] = __byte_perm(t0.y, t1.y, 0x7632);
            };
            auto flush_group = [&](const uint32_t (&hN)[2], const uint32_t (&hD)[2]) {
                uint32_t z[2];
#pragma unroll
                for (int r = 0; r < 2; r++) {
                    const float d0 = h_lo(hD[r]), d1 = h_hi(hD[r]);
                    const float rr = rcp(d0 * d1);
                    uint32_t r2;
                    asm("cvt.rn.satfinite.f16x2.f32 %0, %1, %2;" : "=r"(r2) : "f"(rr * d0), "f"(rr * d1));
                    z[r] = hfma2(hN[r], r2, u2[r]);
                }
                const uint32_t o0 = finish2(h_lo(z[0]), h_lo(z[1]), x2[0]), o1 = finish2(h_hi(z[0]), h_hi(z[1]), x2[1]);
                asm volatile("st.global.u32 [%0], %1;" ::"l"(reinterpret_cast<char*>(p.out) + ro[0]), "r"(o0) : "memory");
                asm volatile("st.global.u32 [%0], %1;" ::"l"(reinterpret_cast<char*>(p.out) + ro[1]), "r"(o1) : "memory");
                zmax = hamax2(zmax, hamax2(z[0], z[1]));
                flags = __funnelshift_r(flags, flags, 1) ^ (~(__vminu2(hD[0], hD[1]) + (0x80008000u - DEN_SMALL)) & 0x80008000u);
            };
            auto gate = [&](uint32_t g) { return pack_h(1.f + tanh_(h_lo(g)), 1.f + tanh_(h_hi(g))); };
            uint32_t db[2 * NSTEP], dv[2 * NSTEP];
            fetch_group();
            next_a();
            next_rows();
            hN[0] = hN[1] = 0; hD[0] = hD[1] = DEN0;
            if (wg == NWG - 1) bar_arrive<1, 288>();
            const uint32_t mend = ma + 4 * T;
#pragma unroll 1
            while (ma != mend) {
                uint32_t m;
                asm volatile("ld.shared.u32 %0, [%1];" : "=r"(m) : "r"(ma));
                ma += 4;
                bar_sync<288>(turn);
                wg_fence();
                mma_rs<0, 0>(dv, fv, dx);
                mma_rs<0, 0>(db, fb, dx);
#pragma unroll
                for (int k = 1; k < 4; k++) {
                    mma_rs<1, 0>(dv, fv + 4 * k, dx + 2 * k);
                    mma_rs<1, 0>(db, fb + 4 * k, dx + 2 * k);
                }
                mma_rs<1, 1>(db, fe, de);
                wg_commit();
                dx ^= TB >> 4;
                de ^= 128;
                auto block = [&](int e) {
                    bar_arrive<288>(next);
                    if (e > 0) {
                        asm volatile("ld.global.nc.u32 %0, [%1];" : "=r"(x2[0]) : "l"(reinterpret_cast<const char*>(p.x) + ro[0]));
                        asm volatile("ld.global.nc.u32 %0, [%1];" : "=r"(x2[1]) : "l"(reinterpret_cast<const char*>(p.x) + ro[1]));
                        fetch_group();
                    }
                    wg_wait();
                    keep(dv); keep(db); keep(fe);
                    if (e > 0) next_a();
                    uint32_t oN[2], oD[2];
#pragma unroll
                    for (int j = 0; j < NSTEP; j++) {
#pragma unroll
                        for (int r = 0; r < 2; r++) {
                            const uint32_t w = gate(e > 0 && j >= e ? hadd2(db[2 * j + r], hA[r]) : db[2 * j + r]);
                            hN[r] = hfma2(w, dv[2 * j + r], hN[r]);
                            hD[r] = hadd2(w, hD[r]);
                        }
                        if (j + 1 == e) {
                            oN[0] = hN[0]; oN[1] = hN[1]; oD[0] = hD[0]; oD[1] = hD[1];
                            hN[0] = hN[1] = 0; hD[0] = hD[1] = DEN0;
                        }
                    }
                    if (e > 0) { flush_group(oN, oD); next_rows(); }
                };
                if (m == 0) block(0);
                else if (m > 4) { if (m > 6) { if (m > 7) block(8); else block(7); } else { if (m > 5) block(6); else block(5); } }
                else { if (m > 2) { if (m > 3) block(4); else block(3); } else { if (m > 1) block(2); else block(1); } }
            }
            for (uint32_t i = T, n = max_tiles(); i < n; i++) {
                bar_sync<288>(turn);
                bar_arrive<288>(next);
            }
            if (wg == 0) bar_sync<1, 288>();
            if (__any_sync(0xffffffffu, flags != 0)) redo_small(p.x, p.wb, p.wv, p.wc, p.out, flags, wg, node0);
            asm volatile("{\n.reg .pred q;\nsetp.ge.u32 q, %1, 0x7c00;\nbar.red.or.pred q, %2, %3, q;\nselp.u32 %0, 1, 0, q;\n}"
                         : "=r"(plain) : "r"(hmag(zmax) | s_misc[M_LATE] << 15), "n"((int)B_FINAL), "n"(NT) : "memory");
        }
        if (plain) slow_bin(p, sm, node0, nvalid);
    }
}

typedef CUresult (*EncodeFn)(CUtensorMap*, CUtensorMapDataType, cuuint32_t, void*, const cuuint64_t*, const cuuint64_t*,
                             const cuuint32_t*, const cuuint32_t*, CUtensorMapInterleave, CUtensorMapSwizzle,
                             CUtensorMapL2promotion, CUtensorMapFloatOOBfill);

}

extern "C" void kernel_launch(void* const* d_in, const int* in_sizes, int n_in, void* d_out, int out_size) {
    static int sms = 0;
    static EncodeFn encode = nullptr;
    static void *cell = nullptr, *ext = nullptr, *cnt = nullptr, *x16 = nullptr, *len = nullptr;
    if (!sms) {
        int dev = 0;
        cudaGetDevice(&dev);
        cudaDeviceGetAttribute(&sms, cudaDevAttrMultiProcessorCount, dev);
        cudaFuncSetAttribute(gatedgcn_kernel<1>, cudaFuncAttributeMaxDynamicSharedMemorySize, SM_TOTAL);
        cudaFuncSetAttribute(gatedgcn_kernel<2>, cudaFuncAttributeMaxDynamicSharedMemorySize, SM_TOTAL);
        cudaFuncSetAttribute(gatedgcn_kernel<3>, cudaFuncAttributeMaxDynamicSharedMemorySize, SM_TOTAL);
        cudaDriverEntryPointQueryResult qr;
        cudaGetDriverEntryPoint("cuTensorMapEncodeTiled", (void**)&encode, cudaEnableDefault, &qr);
        cudaGetSymbolAddress(&cell, g_cell);
        cudaGetSymbolAddress(&ext, g_ext);
        cudaGetSymbolAddress(&cnt, g_cnt);
        cudaGetSymbolAddress(&len, g_len);
        cudaGetSymbolAddress(&x16, g_x16);
        if (((uint64_t)x16 >> 32) != (((uint64_t)x16 + G * NSLOT * 128 - 1) >> 32)) x16 = (char*)x16 + G * NSLOT * 128;
    }
    Params p;
    p.x = (const __nv_bfloat16*)d_in[0];
    p.e = (const __nv_bfloat16*)d_in[1];
    p.src = (const int*)d_in[2];
    p.dst = (const int*)d_in[3];
    p.wa = (const __nv_bfloat16*)d_in[4];
    p.wb = (const __nv_bfloat16*)d_in[5];
    p.wc = (const __nv_bfloat16*)d_in[6];
    p.wu = (const __nv_bfloat16*)d_in[7];
    p.wv = (const __nv_bfloat16*)d_in[8];
    p.out = (__nv_bfloat16*)d_out;
    p.cell = (uint4*)cell;
    p.ext = (uint64_t*)ext;
    p.len = (uint32_t*)len;
    p.cnt = (uint32_t*)cnt;
    p.x16 = (const uint4*)x16;
    p.N = in_sizes[0] / 64;
    p.E = in_sizes[2];
    p.npc = (p.N + G - 1) / G;
    p.chunk = ((p.E + G - 1) / G + 7) & ~7;
    p.magic = (uint32_t)(0x100000000ull / (uint32_t)p.npc) + 1u;
    if (!encode || p.npc > NROW || p.N - (G - 1) * p.npc < 8 * NWG || p.chunk > CHUNK_MAX || (p.E & 7) ||
        p.E - (G - 1) * p.chunk <= (NWG - 1) * VWG * 4) return;

    CUtensorMap xmap, hmap;
    const cuuint64_t dims[2] = {64, (cuuint64_t)p.N};
    const cuuint64_t strides[1] = {128};
    const cuuint32_t box[2] = {64, XROWS}, estr[2] = {1, 1};
    encode(&xmap, CU_TENSOR_MAP_DATA_TYPE_BFLOAT16, 2, d_in[0], dims, strides, box, estr, CU_TENSOR_MAP_INTERLEAVE_NONE,
           CU_TENSOR_MAP_SWIZZLE_128B, CU_TENSOR_MAP_L2_PROMOTION_L2_256B, CU_TENSOR_MAP_FLOAT_OOB_FILL_NONE);
    encode(&hmap, CU_TENSOR_MAP_DATA_TYPE_FLOAT16, 2, x16, dims, strides, box, estr, CU_TENSOR_MAP_INTERLEAVE_NONE,
           CU_TENSOR_MAP_SWIZZLE_128B, CU_TENSOR_MAP_L2_PROMOTION_NONE, CU_TENSOR_MAP_FLOAT_OOB_FILL_NONE);
    if (sms >= G) {
        gatedgcn_kernel<3><<<G, NTA, SM_TOTAL>>>(p, xmap, hmap);
    } else {
        gatedgcn_kernel<1><<<G, NTA, SM_TOTAL>>>(p, xmap, hmap);
        gatedgcn_kernel<2><<<G, NTA, SM_TOTAL>>>(p, xmap, hmap);
    }
}
```
